```python
import torch

def _softmax(x, axis=-1):
    return torch.softmax(x, dim=axis)

def _gelu(x):
    return torch.nn.functional.gelu(x, approximate='tanh')

def _silu(x):
    return torch.nn.functional.silu(x)

def _sigmoid(x):
    return torch.sigmoid(x)

def _layernorm(x, axis=-1, eps=1e-05):
    m = x.mean(dim=axis, keepdim=True)
    v = x.var(dim=axis, keepdim=True, unbiased=False)
    return (x - m) / torch.sqrt(v + eps)

def _scatter_add(tgt, idx, src, axis=0):
    return tgt.clone().index_add_(axis, idx, src)

def _segment_sum(src, seg, n):
    out = torch.zeros((n,) + src.shape[1:], dtype=src.dtype)
    return out.index_add_(0, seg, src)

def _pad(x, pw):
    flat = tuple((v for pair in reversed(pw) for v in pair))
    return torch.nn.functional.pad(x, flat)
kernel_name = 'adaLN_cond__softmax_full_mha__glu_gated_glu__prompt'

def setup_inputs():

    _w = lambda a: (lambda t: t.to(torch.bfloat16) if t.is_floating_point() else t)(torch.as_tensor(a))

    def _A_setup():
        B, S, D = (1, 2048, 512)
        return {'x': _w((lambda *s: torch.randn(*s, dtype=torch.bfloat16) * 0.05)(B, S, D)), 'wqkv': _w((lambda *s: torch.randn(*s, dtype=torch.bfloat16) * 0.05)(D, 3 * D)), 'wo': _w((lambda *s: torch.randn(*s, dtype=torch.bfloat16) * 0.05)(D, D))}
    _A_in = _A_setup()

    def _B_setup():
        B, S, D, F = (1, 2048, 512, 1792)
        return {'x': _w((lambda *s: torch.randn(*s, dtype=torch.bfloat16) * 0.05)(B, S, D)), 'w_gate': _w((lambda *s: torch.randn(*s, dtype=torch.bfloat16) * 0.05)(D, F)), 'w_up': _w((lambda *s: torch.randn(*s, dtype=torch.bfloat16) * 0.05)(D, F)), 'w_down': _w((lambda *s: torch.randn(*s, dtype=torch.bfloat16) * 0.05)(F, D))}
    _B_in = _B_setup()
    return {'A_x': _A_in['x'], 'A_wqkv': _A_in['wqkv'], 'A_wo': _A_in['wo'], 'B_x': _B_in['x'], 'B_w_gate': _B_in['w_gate'], 'B_w_up': _B_in['w_up'], 'B_w_down': _B_in['w_down'], 'c': _w((lambda *s: torch.randn(*s, dtype=torch.bfloat16) * 0.1)(1, 512) * 8.0), 'w_mod': _w((lambda *s: torch.randn(*s, dtype=torch.bfloat16) * 0.1)(512, 6 * 512) * 512 ** (-0.5) * 8.0)}

def reference(A_x, A_wqkv, A_wo, B_x, B_w_gate, B_w_up, B_w_down, c, w_mod):

    def _A_ref(x, wqkv, wo):
        B, S, D = x.shape
        H = 32
        Dh = D // H
        qkv = (lambda x, *d: x.permute(*d))((x @ wqkv).reshape(B, S, 3, H, Dh), 2, 0, 3, 1, 4)
        q, k, v = (qkv[0], qkv[1], qkv[2])
        scale = Dh ** (-0.5)
        scores = torch.einsum('bhqd,bhkd->bhqk', q, k) * scale
        p = _softmax(scores, axis=-1)
        o = torch.einsum('bhqk,bhkd->bhqd', p, v)
        return (lambda x, *d: x.permute(*d))(o, 0, 2, 1, 3).reshape(B, S, D) @ wo

    def _B_ref(x, w_gate, w_up, w_down):
        g = torch.einsum('bsd,df->bsf', x, w_gate)
        u = torch.einsum('bsd,df->bsf', x, w_up)
        h = _sigmoid(g) * u
        return torch.einsum('bsf,fd->bsd', h, w_down)
    x = A_x
    mod = (_silu(c) @ w_mod).reshape(c.shape[0], 6, 1, -1)
    sa, ca, ga, sb, cb, gb = (mod[:, 0].clone(), mod[:, 1].clone(), mod[:, 2].clone(), mod[:, 3].clone(), mod[:, 4].clone(), mod[:, 5].clone())
    h = _layernorm(x, axis=-1) * (1 + ca) + sa
    x = x + ga * _A_ref(h, A_wqkv, A_wo)
    h = _layernorm(x, axis=-1) * (1 + cb) + sb
    x = x + gb * _B_ref(h, B_w_gate, B_w_up, B_w_down)
    return x
```

```cpp
#include <cuda_runtime.h>
#include <cuda_bf16.h>
#include <cuda_fp16.h>
#include <cuda.h>
#include <stdint.h>
#include <stddef.h>

typedef __nv_bfloat16 bf16;

constexpr int AUX_BYTES = 7680;
struct __align__(1024) Scratch {
    unsigned epoch[256];
    unsigned flag[24 * 32];
    uint64_t modll[512];
    uint64_t lnll[2048];
    bf16 mod2[2048];
    uint64_t time[128];
    uint8_t aux[8 * AUX_BYTES];
    float nrm[8 * 128];
    uint4 stat[128 * 128];
    uint8_t kv[8 * 2 * 16 * 16384];
    uint8_t o[2 * 128 * 8192];
    uint8_t y[128 * 16384];
    uint8_t act[16 * 112 * 4096];
    uint4 kp[128 * 2 * 512];
    uint4 qb[128 * 2 * 512];
};
__device__ Scratch g_scratch;
#define STAMP(i) do {} while (0)
#define MARK(i) sched_fence()
constexpr int F_KV = 0;
constexpr int F_GRP = 8;
constexpr int F_AUX = 16;

struct __align__(64) Params {
    const bf16 *x, *c, *wmod;
    Scratch* S;
    uint64_t hH, hSW64, hSW128, hCORE, hAux, hK[2], hV[2];
    uint32_t cM, pad;
    const bf16 *wqkv, *wo, *wg, *wu, *wd;
    CUtensorMap tKV, tQ, tAK, tAV, tWo, tX, tG, tU, tGn, tUn, tD, tOut;
};

constexpr uint32_t SB = 1024;
constexpr int SM_R0 = 0, SM_R1 = 65536, SM_RING = 131072, SM_SCR = 212992;
constexpr int SM_XT = SM_SCR, SM_AUX = SM_SCR, SM_AB = SM_SCR + 8192, SM_MV = SM_SCR + 16384;
constexpr int SM_GS = SM_SCR, SM_RED = SM_SCR + 2048, SM_C = SM_SCR + 2560, SM_WM = SM_SCR + 4096;
constexpr int SM_K = SM_RING, SM_ONES = SM_RING + 32768, SM_V0 = SM_RING + 49152;
constexpr uint64_t P1SLOT = 0x104321504321ull;
constexpr int SM_BAR = 229888, SM_EP = SM_BAR + 2048, SM_KM = SM_EP + 16;
constexpr int SM_TOTAL = 232448;
constexpr int B_P1F = 0, B_ATF = 12, B_WO = 16, B_O0 = 17, B_AUX = 18, B_STG = 19, B_KM = 20, B_WF = 21, B_PF = 49, B_Y = 77, B_KSG = 85,
              B_PL = 86, B_YF = 87, B_SEN = 88, B_MV = 89, B_P1G = 90;
constexpr int B_END = 91, B_PE = 92, B_AV = 113, B_P1E = 121, B_H = 133, B_HI = 137, B_KST = 141, B_QX = 142, B_ONE = 143;
constexpr int B_WE = 144, B_ACT = 172, B_AB = 176, B_KP = 177;
constexpr int B_ATE = 178, B_OD = 182, B_P3H = 184, B_P3D = 185, B_YD = 186, B_YS = 187, B_GSD = 188, B_X2 = 189, B_NUM = 190;
constexpr int B_X = 192;

#define TAU 275
#define G8 5200
#define ADEL 1600
#define PACE 50
#define PACE2 70

__device__ __forceinline__ void mma_ss64(float (&d)[32], uint64_t da, uint64_t db) {
    asm volatile("wgmma.mma_async.sync.aligned.m64n64k16.f32.bf16.bf16 {%0, %1, %2, %3, %4, %5, %6, %7, %8, %9, %10, %11, %12, %13, %14, %15, %16, %17, %18, %19, %20, %21, %22, %23, %24, %25, %26, %27, %28, %29, %30, %31}, %32, %33, 1, 1, 1, 0, 1;"
        : "+f"(d[0]), "+f"(d[1]), "+f"(d[2]), "+f"(d[3]), "+f"(d[4]), "+f"(d[5]), "+f"(d[6]), "+f"(d[7]), "+f"(d[8]), "+f"(d[9]), "+f"(d[10]), "+f"(d[11]), "+f"(d[12]), "+f"(d[13]), "+f"(d[14]), "+f"(d[15]), "+f"(d[16]), "+f"(d[17]), "+f"(d[18]), "+f"(d[19]), "+f"(d[20]), "+f"(d[21]), "+f"(d[22]), "+f"(d[23]), "+f"(d[24]), "+f"(d[25]), "+f"(d[26]), "+f"(d[27]), "+f"(d[28]), "+f"(d[29]), "+f"(d[30]), "+f"(d[31])
        : "l"(da), "l"(db));
}
__device__ __forceinline__ void mma_ss128(float (&d)[64], uint64_t da, uint64_t db) {
    asm volatile("wgmma.mma_async.sync.aligned.m64n128k16.f32.bf16.bf16 {%0, %1, %2, %3, %4, %5, %6, %7, %8, %9, %10, %11, %12, %13, %14, %15, %16, %17, %18, %19, %20, %21, %22, %23, %24, %25, %26, %27, %28, %29, %30, %31, %32, %33, %34, %35, %36, %37, %38, %39, %40, %41, %42, %43, %44, %45, %46, %47, %48, %49, %50, %51, %52, %53, %54, %55, %56, %57, %58, %59, %60, %61, %62, %63}, %64, %65, 1, 1, 1, 0, 1;"
        : "+f"(d[0]), "+f"(d[1]), "+f"(d[2]), "+f"(d[3]), "+f"(d[4]), "+f"(d[5]), "+f"(d[6]), "+f"(d[7]), "+f"(d[8]), "+f"(d[9]), "+f"(d[10]), "+f"(d[11]), "+f"(d[12]), "+f"(d[13]), "+f"(d[14]), "+f"(d[15]), "+f"(d[16]), "+f"(d[17]), "+f"(d[18]), "+f"(d[19]), "+f"(d[20]), "+f"(d[21]), "+f"(d[22]), "+f"(d[23]), "+f"(d[24]), "+f"(d[25]), "+f"(d[26]), "+f"(d[27]), "+f"(d[28]), "+f"(d[29]), "+f"(d[30]), "+f"(d[31]), "+f"(d[32]), "+f"(d[33]), "+f"(d[34]), "+f"(d[35]), "+f"(d[36]), "+f"(d[37]), "+f"(d[38]), "+f"(d[39]), "+f"(d[40]), "+f"(d[41]), "+f"(d[42]), "+f"(d[43]), "+f"(d[44]), "+f"(d[45]), "+f"(d[46]), "+f"(d[47]), "+f"(d[48]), "+f"(d[49]), "+f"(d[50]), "+f"(d[51]), "+f"(d[52]), "+f"(d[53]), "+f"(d[54]), "+f"(d[55]), "+f"(d[56]), "+f"(d[57]), "+f"(d[58]), "+f"(d[59]), "+f"(d[60]), "+f"(d[61]), "+f"(d[62]), "+f"(d[63])
        : "l"(da), "l"(db));
}
__device__ __forceinline__ void mma_ss128t(float (&d)[64], uint64_t da, uint64_t db) {
    asm volatile("wgmma.mma_async.sync.aligned.m64n128k16.f32.bf16.bf16 {%0, %1, %2, %3, %4, %5, %6, %7, %8, %9, %10, %11, %12, %13, %14, %15, %16, %17, %18, %19, %20, %21, %22, %23, %24, %25, %26, %27, %28, %29, %30, %31, %32, %33, %34, %35, %36, %37, %38, %39, %40, %41, %42, %43, %44, %45, %46, %47, %48, %49, %50, %51, %52, %53, %54, %55, %56, %57, %58, %59, %60, %61, %62, %63}, %64, %65, 1, 1, 1, 1, 0;"
        : "+f"(d[0]), "+f"(d[1]), "+f"(d[2]), "+f"(d[3]), "+f"(d[4]), "+f"(d[5]), "+f"(d[6]), "+f"(d[7]), "+f"(d[8]), "+f"(d[9]), "+f"(d[10]), "+f"(d[11]), "+f"(d[12]), "+f"(d[13]), "+f"(d[14]), "+f"(d[15]), "+f"(d[16]), "+f"(d[17]), "+f"(d[18]), "+f"(d[19]), "+f"(d[20]), "+f"(d[21]), "+f"(d[22]), "+f"(d[23]), "+f"(d[24]), "+f"(d[25]), "+f"(d[26]), "+f"(d[27]), "+f"(d[28]), "+f"(d[29]), "+f"(d[30]), "+f"(d[31]), "+f"(d[32]), "+f"(d[33]), "+f"(d[34]), "+f"(d[35]), "+f"(d[36]), "+f"(d[37]), "+f"(d[38]), "+f"(d[39]), "+f"(d[40]), "+f"(d[41]), "+f"(d[42]), "+f"(d[43]), "+f"(d[44]), "+f"(d[45]), "+f"(d[46]), "+f"(d[47]), "+f"(d[48]), "+f"(d[49]), "+f"(d[50]), "+f"(d[51]), "+f"(d[52]), "+f"(d[53]), "+f"(d[54]), "+f"(d[55]), "+f"(d[56]), "+f"(d[57]), "+f"(d[58]), "+f"(d[59]), "+f"(d[60]), "+f"(d[61]), "+f"(d[62]), "+f"(d[63])
        : "l"(da), "l"(db));
}
__device__ __forceinline__ void mma_rs64(float (&d)[32], const uint32_t (&a)[4], uint64_t db) {
    asm volatile("wgmma.mma_async.sync.aligned.m64n64k16.f32.bf16.bf16 {%0, %1, %2, %3, %4, %5, %6, %7, %8, %9, %10, %11, %12, %13, %14, %15, %16, %17, %18, %19, %20, %21, %22, %23, %24, %25, %26, %27, %28, %29, %30, %31}, {%32,%33,%34,%35}, %36, 1, 1, 1, 0;"
        : "+f"(d[0]), "+f"(d[1]), "+f"(d[2]), "+f"(d[3]), "+f"(d[4]), "+f"(d[5]), "+f"(d[6]), "+f"(d[7]), "+f"(d[8]), "+f"(d[9]), "+f"(d[10]), "+f"(d[11]), "+f"(d[12]), "+f"(d[13]), "+f"(d[14]), "+f"(d[15]), "+f"(d[16]), "+f"(d[17]), "+f"(d[18]), "+f"(d[19]), "+f"(d[20]), "+f"(d[21]), "+f"(d[22]), "+f"(d[23]), "+f"(d[24]), "+f"(d[25]), "+f"(d[26]), "+f"(d[27]), "+f"(d[28]), "+f"(d[29]), "+f"(d[30]), "+f"(d[31])
        : "r"(a[0]), "r"(a[1]), "r"(a[2]), "r"(a[3]), "l"(db));
}
__device__ __forceinline__ void mma_rs128(float (&d)[64], const uint32_t (&a)[4], uint64_t db) {
    asm volatile("wgmma.mma_async.sync.aligned.m64n128k16.f32.bf16.bf16 {%0, %1, %2, %3, %4, %5, %6, %7, %8, %9, %10, %11, %12, %13, %14, %15, %16, %17, %18, %19, %20, %21, %22, %23, %24, %25, %26, %27, %28, %29, %30, %31, %32, %33, %34, %35, %36, %37, %38, %39, %40, %41, %42, %43, %44, %45, %46, %47, %48, %49, %50, %51, %52, %53, %54, %55, %56, %57, %58, %59, %60, %61, %62, %63}, {%64,%65,%66,%67}, %68, 1, 1, 1, 0;"
        : "+f"(d[0]), "+f"(d[1]), "+f"(d[2]), "+f"(d[3]), "+f"(d[4]), "+f"(d[5]), "+f"(d[6]), "+f"(d[7]), "+f"(d[8]), "+f"(d[9]), "+f"(d[10]), "+f"(d[11]), "+f"(d[12]), "+f"(d[13]), "+f"(d[14]), "+f"(d[15]), "+f"(d[16]), "+f"(d[17]), "+f"(d[18]), "+f"(d[19]), "+f"(d[20]), "+f"(d[21]), "+f"(d[22]), "+f"(d[23]), "+f"(d[24]), "+f"(d[25]), "+f"(d[26]), "+f"(d[27]), "+f"(d[28]), "+f"(d[29]), "+f"(d[30]), "+f"(d[31]), "+f"(d[32]), "+f"(d[33]), "+f"(d[34]), "+f"(d[35]), "+f"(d[36]), "+f"(d[37]), "+f"(d[38]), "+f"(d[39]), "+f"(d[40]), "+f"(d[41]), "+f"(d[42]), "+f"(d[43]), "+f"(d[44]), "+f"(d[45]), "+f"(d[46]), "+f"(d[47]), "+f"(d[48]), "+f"(d[49]), "+f"(d[50]), "+f"(d[51]), "+f"(d[52]), "+f"(d[53]), "+f"(d[54]), "+f"(d[55]), "+f"(d[56]), "+f"(d[57]), "+f"(d[58]), "+f"(d[59]), "+f"(d[60]), "+f"(d[61]), "+f"(d[62]), "+f"(d[63])
        : "r"(a[0]), "r"(a[1]), "r"(a[2]), "r"(a[3]), "l"(db));
}
__device__ __forceinline__ void mma_rs64t(float (&d)[32], const uint32_t (&a)[4], uint64_t db) {
    asm volatile("wgmma.mma_async.sync.aligned.m64n64k16.f32.bf16.bf16 {%0, %1, %2, %3, %4, %5, %6, %7, %8, %9, %10, %11, %12, %13, %14, %15, %16, %17, %18, %19, %20, %21, %22, %23, %24, %25, %26, %27, %28, %29, %30, %31}, {%32,%33,%34,%35}, %36, 1, 1, 1, 1;"
        : "+f"(d[0]), "+f"(d[1]), "+f"(d[2]), "+f"(d[3]), "+f"(d[4]), "+f"(d[5]), "+f"(d[6]), "+f"(d[7]), "+f"(d[8]), "+f"(d[9]), "+f"(d[10]), "+f"(d[11]), "+f"(d[12]), "+f"(d[13]), "+f"(d[14]), "+f"(d[15]), "+f"(d[16]), "+f"(d[17]), "+f"(d[18]), "+f"(d[19]), "+f"(d[20]), "+f"(d[21]), "+f"(d[22]), "+f"(d[23]), "+f"(d[24]), "+f"(d[25]), "+f"(d[26]), "+f"(d[27]), "+f"(d[28]), "+f"(d[29]), "+f"(d[30]), "+f"(d[31])
        : "r"(a[0]), "r"(a[1]), "r"(a[2]), "r"(a[3]), "l"(db));
}
__device__ __forceinline__ void mma_qk(float (&d)[32], const uint32_t (&a)[4], uint64_t db) {
    asm volatile("wgmma.mma_async.sync.aligned.m64n64k16.f32.f16.f16 {%0, %1, %2, %3, %4, %5, %6, %7, %8, %9, %10, %11, %12, %13, %14, %15, %16, %17, %18, %19, %20, %21, %22, %23, %24, %25, %26, %27, %28, %29, %30, %31}, {%32,%33,%34,%35}, %36, 1, 1, 1, 1;"
        : "+f"(d[0]), "+f"(d[1]), "+f"(d[2]), "+f"(d[3]), "+f"(d[4]), "+f"(d[5]), "+f"(d[6]), "+f"(d[7]), "+f"(d[8]), "+f"(d[9]), "+f"(d[10]), "+f"(d[11]), "+f"(d[12]), "+f"(d[13]), "+f"(d[14]), "+f"(d[15]), "+f"(d[16]), "+f"(d[17]), "+f"(d[18]), "+f"(d[19]), "+f"(d[20]), "+f"(d[21]), "+f"(d[22]), "+f"(d[23]), "+f"(d[24]), "+f"(d[25]), "+f"(d[26]), "+f"(d[27]), "+f"(d[28]), "+f"(d[29]), "+f"(d[30]), "+f"(d[31])
        : "r"(a[0]), "r"(a[1]), "r"(a[2]), "r"(a[3]), "l"(db));
}
__device__ __forceinline__ void mma_pv(float (&d)[12], const uint32_t (&a)[4], uint64_t db) {
    asm volatile("wgmma.mma_async.sync.aligned.m64n24k16.f32.bf16.bf16 {%0, %1, %2, %3, %4, %5, %6, %7, %8, %9, %10, %11}, {%12,%13,%14,%15}, %16, 1, 1, 1, 0;"
        : "+f"(d[0]), "+f"(d[1]), "+f"(d[2]), "+f"(d[3]), "+f"(d[4]), "+f"(d[5]), "+f"(d[6]), "+f"(d[7]), "+f"(d[8]), "+f"(d[9]), "+f"(d[10]), "+f"(d[11])
        : "r"(a[0]), "r"(a[1]), "r"(a[2]), "r"(a[3]), "l"(db));
}

__device__ __forceinline__ void wg_fence() { asm volatile("wgmma.fence.sync.aligned;" ::: "memory"); }
__device__ __forceinline__ void wg_commit() { asm volatile("wgmma.commit_group.sync.aligned;" ::: "memory"); }
template <int N> __device__ __forceinline__ void wg_wait() { asm volatile("wgmma.wait_group.sync.aligned %0;" ::"n"(N) : "memory"); }
template <int N> __device__ __forceinline__ void pin(float (&d)[N]) {
#pragma unroll
    for (int i = 0; i < N; i++) asm volatile("" : "+f"(d[i])::"memory");
}
template <int N> __device__ __forceinline__ void pin(uint32_t (&d)[N][4]) {
#pragma unroll
    for (int i = 0; i < N; i++) asm volatile("" : "+r"(d[i][0]), "+r"(d[i][1]), "+r"(d[i][2]), "+r"(d[i][3])::"memory");
}
template <int N> __device__ __forceinline__ void zero(float (&d)[N]) {
#pragma unroll
    for (int i = 0; i < N; i++) d[i] = 0.f;
    pin(d);
}
__host__ __device__ constexpr uint32_t dlo(uint32_t off, uint32_t lbo) { return ((SB + off) >> 4) | ((lbo >> 4) << 16); }
__host__ __device__ constexpr uint64_t dhi(uint32_t sbo, uint32_t swz) { return (uint64_t)((sbo >> 4) | (swz << 30)) << 32; }
__device__ __forceinline__ void mbar_init(uint32_t bar, uint32_t cnt) { asm volatile("mbarrier.init.shared::cta.b64 [%0], %1;" ::"r"(bar), "r"(cnt) : "memory"); }
__device__ __forceinline__ void mbar_expect(uint32_t bar, uint32_t bytes) { asm volatile("mbarrier.arrive.expect_tx.shared::cta.b64 _, [%0], %1;" ::"r"(bar), "r"(bytes) : "memory"); }
__device__ __forceinline__ void mbar_arrive(uint32_t bar) { asm volatile("mbarrier.arrive.shared::cta.b64 _, [%0];" ::"r"(bar) : "memory"); }
__device__ __forceinline__ void mbar_spin(uint32_t bar, uint32_t parity) {
    asm volatile("{\n.reg .pred p;\nLW:\nmbarrier.try_wait.parity.shared::cta.b64 p, [%0], %1;\n@!p bra.uni LW;\n}" ::"r"(bar), "r"(parity) : "memory");
}
__device__ __forceinline__ void mbar_nap(uint32_t bar) {
    asm volatile("{\n.reg .pred p;\nLW:\nmbarrier.test_wait.parity.shared::cta.b64 p, [%0], 0;\n@p bra.uni LD;\nnanosleep.u32 400;\nbra.uni LW;\nLD:\n}" ::"r"(bar) : "memory");
}
__device__ __forceinline__ void mbar_wait(uint32_t bar, uint32_t nap) {
    asm volatile(
        "{\n.reg .pred p;\n.reg .u32 t0, t1;\n"
        "mov.u32 t0, %%clock;\n"
        "LW:\nmbarrier.try_wait.parity.shared::cta.b64 p, [%0], 0;\n@p bra.uni LD;\nnanosleep.u32 %1;\n"
        "mov.u32 t1, %%clock;\nsub.u32 t1, t1, t0;\nsetp.lt.u32 p, t1, 0x70000000;\n@p bra.uni LW;\ntrap;\nLD:\n}" ::"r"(bar), "r"(nap) : "memory");
}
__device__ __forceinline__ void trap_if(bool c) { asm volatile("{.reg .pred p; setp.ne.u32 p, %0, 0; @p trap;}" ::"r"((uint32_t)c)); }
#define EXIT() do { asm volatile("exit;"); __builtin_unreachable(); } while (0)
__device__ __forceinline__ bool elect() {
    uint32_t p;
    asm volatile("{.reg .pred P; elect.sync _|P, 0xffffffff; selp.u32 %0, 1, 0, P;}" : "=r"(p));
    return p;
}
__device__ __forceinline__ uint32_t uni(uint32_t x) { uint32_t r; asm volatile("shfl.sync.idx.b32 %0, %1, 0, 31, 0xffffffff;" : "=r"(r) : "r"(x)); return r; }
__device__ __forceinline__ int rd_tid() { int r; asm volatile("mov.u32 %0, %%tid.x;" : "=r"(r)); return r; }
__device__ __forceinline__ int rd_cta() { int r; asm volatile("mov.u32 %0, %%ctaid.x;" : "=r"(r)); return r - (((r + 16) >> 7) << 1); }
#define IDS()                                                                                                          \
    const int tid = rd_tid(), lane = tid & 31, warp = uni(tid >> 5), mi = rd_cta(), rb = mi >> 3, cg = mi & 7;          \
    const int w = warp & 3, m = (warp >> 2) & 1, n = warp >> 3, g = lane >> 2, t = lane & 3;                           \
    const uint32_t tile = (m * 8 + w * 2) * 256;                                                                       \
    (void)rb; (void)cg; (void)n; (void)g; (void)t; (void)tile
__device__ __forceinline__ void release(uint32_t bar) { if ((threadIdx.x & 31) == 0) mbar_arrive(bar); }
__device__ __forceinline__ void warp_arrive(uint32_t bar) { __syncwarp(); release(bar); }
__device__ __forceinline__ void sched_fence() { asm volatile("pmevent 0;" ::: "memory"); }
__device__ __forceinline__ void bar_sync(int id, int n) { asm volatile("bar.sync %0, %1;" ::"r"(id), "r"(n) : "memory"); }
__device__ __forceinline__ void fence_async_smem() { asm volatile("fence.proxy.async.shared::cta;" ::: "memory"); }
__device__ __forceinline__ void bulk_ld(uint32_t dst, const void* src, uint32_t bytes, uint32_t bar) {
    asm volatile("cp.async.bulk.shared::cluster.global.mbarrier::complete_tx::bytes [%0], [%1], %2, [%3];" ::"r"(dst), "l"(src), "r"(bytes), "r"(bar) : "memory");
}
__device__ __forceinline__ void bulk_st(void* dst, uint32_t src, uint32_t bytes) {
    asm volatile("cp.async.bulk.global.shared::cta.bulk_group [%0], [%1], %2;" ::"l"(dst), "r"(src), "r"(bytes) : "memory");
}
__device__ __forceinline__ void bulk_st_wait() { asm volatile("cp.async.bulk.commit_group;\ncp.async.bulk.wait_group 0;" ::: "memory"); }
__device__ __forceinline__ void l2_prefetch(const void* src, uint32_t bytes) { asm volatile("cp.async.bulk.prefetch.L2.global [%0], %1;" ::"l"(src), "r"(bytes) : "memory"); }
__device__ __forceinline__ void tma2d(uint32_t dst, const CUtensorMap* tm, uint32_t bar, int x, int y) {
    asm volatile("cp.async.bulk.tensor.2d.shared::cluster.global.mbarrier::complete_tx::bytes [%0], [%1, {%3, %4}], [%2];" ::"r"(dst), "l"(tm), "r"(bar), "r"(x), "r"(y) : "memory");
}
__device__ __forceinline__ void tma3d(uint32_t dst, const CUtensorMap* tm, uint32_t bar, int x, int y, int z) {
    asm volatile("cp.async.bulk.tensor.3d.shared::cluster.global.mbarrier::complete_tx::bytes [%0], [%1, {%3, %4, %5}], [%2];" ::"r"(dst), "l"(tm), "r"(bar), "r"(x), "r"(y), "r"(z) : "memory");
}
__device__ __forceinline__ void st_flag(unsigned* p, unsigned v) { asm volatile("st.relaxed.gpu.global.u32 [%0], %1;" ::"l"(p), "r"(v) : "memory"); }
__device__ __forceinline__ void fence_gpu() { asm volatile("fence.release.gpu;" ::: "memory"); }
template <bool BOUNDED = false>
__device__ __forceinline__ void poll_flags(const unsigned* p, int cnt, unsigned want) {
    p += (threadIdx.x & (cnt - 1));
    unsigned v, it = 0;
    do {
        asm volatile("ld.relaxed.gpu.global.u32 %0, [%1];" : "=r"(v) : "l"(p) : "memory");
        if (BOUNDED) trap_if(++it > 3000000u);
    } while (!__all_sync(0xffffffffu, (int)(v - want) >= 0));
    asm volatile("fence.acquire.gpu;\nfence.proxy.async.global;" ::: "memory");
}
__device__ __forceinline__ unsigned now_clk() { unsigned r; asm volatile("mov.u32 %0, %%clock;" : "=r"(r)); return r; }
__device__ __forceinline__ unsigned now_ns() { unsigned r; asm volatile("mov.u32 %0, %%globaltimer_lo;" : "=r"(r)); return r; }
__device__ __forceinline__ void st_ll64(void* p, uint32_t a, uint32_t b) { asm volatile("{.reg .b64 t; mov.b64 t, {%1, %2}; st.relaxed.gpu.global.b64 [%0], t;}" ::"l"(p), "r"(a), "r"(b) : "memory"); }
__device__ __forceinline__ uint2 ld_ll64(const void* p) { uint2 v; asm volatile("{.reg .b64 t; ld.relaxed.gpu.global.b64 t, [%2]; mov.b64 {%0, %1}, t;}" : "=r"(v.x), "=r"(v.y) : "l"(p) : "memory"); return v; }
__device__ __forceinline__ void poll_fast(const unsigned* p, int cnt, unsigned want) {
    p += (threadIdx.x & (cnt - 1));
    unsigned v[4];
#pragma unroll
    for (int i = 0; i < 4; i++) { asm volatile("ld.relaxed.gpu.global.u32 %0, [%1];" : "=r"(v[i]) : "l"(p) : "memory"); if (i < 3) __nanosleep(60); }
    while (true) {
#pragma unroll
        for (int i = 0; i < 4; i++) {
            if (__all_sync(0xffffffffu, (int)(v[i] - want) >= 0)) return;
            asm volatile("ld.relaxed.gpu.global.u32 %0, [%1];" : "=r"(v[i]) : "l"(p) : "memory");
        }
    }
}
__device__ __forceinline__ void rendezvous(uint64_t* slots, int mi, unsigned ep, int delay) {
    const int lane = threadIdx.x & 31;
    const unsigned t0 = now_ns();
    if (lane == 0) st_ll64(slots + mi, t0, ep);
    const uint64_t* p = slots + (mi & ~15) + (lane & 15);
    uint2 v = ld_ll64(p), u;
    __nanosleep(100);
    for (unsigned it = 0;; it++) {
        trap_if(it > 2000000u);
        u = ld_ll64(p);
        if (__all_sync(0xffffffffu, v.y == ep)) break;
        v = ld_ll64(p);
        if (__all_sync(0xffffffffu, u.y == ep)) { v = u; break; }
    }
    const int lag = min(__reduce_max_sync(0xffffffffu, (int)(v.x - t0)), 3000) + delay;
    while ((int)(now_ns() - t0) < lag) {}
}
__device__ __forceinline__ void st_ll128(void* p, uint32_t x, uint32_t y, uint32_t z, uint32_t w) {
    asm volatile("{.reg .b64 a, b; .reg .b128 t; mov.b64 a, {%1, %2}; mov.b64 b, {%3, %4}; mov.b128 t, {a, b}; st.relaxed.gpu.global.b128 [%0], t;}" ::"l"(p), "r"(x), "r"(y), "r"(z), "r"(w) : "memory");
}
__device__ __forceinline__ uint4 ld_ll128(const void* p) {
    uint4 v;
    asm volatile("{.reg .b64 a, b; .reg .b128 t; ld.relaxed.gpu.global.b128 t, [%4]; mov.b128 {a, b}, t; mov.b64 {%0, %1}, a; mov.b64 {%2, %3}, b;}" : "=r"(v.x), "=r"(v.y), "=r"(v.z), "=r"(v.w) : "l"(p) : "memory");
    return v;
}
__device__ __forceinline__ uint32_t pk_bf(float lo, float hi) { uint32_t r; asm("cvt.rn.bf16x2.f32 %0, %1, %2;" : "=r"(r) : "f"(hi), "f"(lo)); return r; }
__device__ __forceinline__ uint32_t pk_h(float lo, float hi) { uint32_t r; asm("cvt.rn.f16x2.f32 %0, %1, %2;" : "=r"(r) : "f"(hi), "f"(lo)); return r; }
__device__ __forceinline__ uint32_t hfma_bf(uint32_t a, uint32_t b, uint32_t c) { uint32_t r; asm("fma.rn.bf16x2 %0, %1, %2, %3;" : "=r"(r) : "r"(a), "r"(b), "r"(c)); return r; }
__device__ __forceinline__ uint32_t hmul_bf(uint32_t a, uint32_t b) { uint32_t r; asm("mul.rn.bf16x2 %0, %1, %2;" : "=r"(r) : "r"(a), "r"(b)); return r; }
__device__ __forceinline__ float bf_lo(uint32_t u) { return __uint_as_float(u << 16); }
__device__ __forceinline__ float bf_hi(uint32_t u) { return __uint_as_float(u & 0xffff0000u); }
__device__ __forceinline__ float bf_round(float v) { return __bfloat162float(__float2bfloat16_rn(v)); }
__device__ __forceinline__ float ex2(float x) { float r; asm("ex2.approx.ftz.f32 %0, %1;" : "=f"(r) : "f"(x)); return r; }
__device__ __forceinline__ float rcp(float x) { float r; asm("rcp.approx.ftz.f32 %0, %1;" : "=f"(r) : "f"(x)); return r; }
__device__ __forceinline__ void sts32(uint32_t a, uint32_t v) { asm volatile("st.shared.u32 [%0], %1;" ::"r"(a), "r"(v) : "memory"); }
__device__ __forceinline__ void sts128(uint32_t a, uint32_t x, uint32_t y, uint32_t z, uint32_t w) { asm volatile("st.shared.v4.u32 [%0], {%1,%2,%3,%4};" ::"r"(a), "r"(x), "r"(y), "r"(z), "r"(w) : "memory"); }
__device__ __forceinline__ void stsm(uint32_t a, uint32_t x, uint32_t y, uint32_t z, uint32_t w) { asm volatile("stmatrix.sync.aligned.m8n8.x4.shared.b16 [%0], {%1,%2,%3,%4};" ::"r"(a), "r"(x), "r"(y), "r"(z), "r"(w) : "memory"); }
__device__ __forceinline__ void stsm_t(uint32_t a, uint32_t x, uint32_t y, uint32_t z, uint32_t w) { asm volatile("stmatrix.sync.aligned.m8n8.x4.trans.shared.b16 [%0], {%1,%2,%3,%4};" ::"r"(a), "r"(x), "r"(y), "r"(z), "r"(w) : "memory"); }
__device__ __forceinline__ uint4 ldsm(uint32_t a) { uint4 v; asm volatile("ldmatrix.sync.aligned.m8n8.x4.shared.b16 {%0,%1,%2,%3}, [%4];" : "=r"(v.x), "=r"(v.y), "=r"(v.z), "=r"(v.w) : "r"(a) : "memory"); return v; }
__device__ __forceinline__ uint4 ldsm_t(uint32_t a) { uint4 v; asm volatile("ldmatrix.sync.aligned.m8n8.x4.trans.shared.b16 {%0,%1,%2,%3}, [%4];" : "=r"(v.x), "=r"(v.y), "=r"(v.z), "=r"(v.w) : "r"(a) : "memory"); return v; }
__device__ __forceinline__ uint4 lds128(uint32_t a) { uint4 v; asm volatile("ld.shared.v4.u32 {%0,%1,%2,%3}, [%4];" : "=r"(v.x), "=r"(v.y), "=r"(v.z), "=r"(v.w) : "r"(a) : "memory"); return v; }
__device__ __forceinline__ float2 lds64f(uint32_t a) { float2 v; asm volatile("ld.shared.v2.f32 {%0,%1}, [%2];" : "=f"(v.x), "=f"(v.y) : "r"(a) : "memory"); return v; }
__device__ __forceinline__ uint32_t lds32(uint32_t a) { uint32_t v; asm volatile("ld.shared.u32 %0, [%1];" : "=r"(v) : "r"(a) : "memory"); return v; }
__device__ __forceinline__ float silu_bf(float v) { return bf_round(v * rcp(1.f + ex2(v * -1.4426950408889634f))); }
__device__ __forceinline__ float reduce8(float (&v)[8], int lane) {
    const bool u4 = lane & 16, u3 = lane & 8, u2 = lane & 4;
#pragma unroll
    for (int j = 0; j < 4; j++) { float s = u4 ? v[j] : v[j + 4], k = u4 ? v[j + 4] : v[j]; v[j] = k + __shfl_xor_sync(0xffffffffu, s, 16); }
#pragma unroll
    for (int j = 0; j < 2; j++) { float s = u3 ? v[j] : v[j + 2], k = u3 ? v[j + 2] : v[j]; v[j] = k + __shfl_xor_sync(0xffffffffu, s, 8); }
    { float s = u2 ? v[0] : v[1], k = u2 ? v[1] : v[0]; v[0] = k + __shfl_xor_sync(0xffffffffu, s, 4); }
    v[0] += __shfl_xor_sync(0xffffffffu, v[0], 2);
    v[0] += __shfl_xor_sync(0xffffffffu, v[0], 1);
    return v[0];
}
__device__ __forceinline__ float quad_sum(float v) { v += __shfl_xor_sync(0xffffffffu, v, 1); v += __shfl_xor_sync(0xffffffffu, v, 2); return v; }

#define PMASK 0x7DD7
#define EXP_MAGIC 445.41764f
__device__ __forceinline__ constexpr bool is_poly(int j) { return (PMASK >> j) & 1; }
#define DUM 0
#define GRP 2
__device__ __forceinline__ void exp_tile(const float (&S)[32], uint32_t (&P)[4][4], uint32_t cM) {
    uint32_t E[16], M[16];
#pragma unroll
    for (int k = 0; k <= 16 / GRP; k++) {
#pragma unroll
        for (int j = k * GRP; j < (k + 1) * GRP && j < 16; j++) {
            if (is_poly(j)) {
                asm("prmt.b32 %0, %1, %2, 0x6521;" : "=r"(E[j]) : "r"(__float_as_uint(S[2 * j])), "r"(__float_as_uint(S[2 * j + 1])));
                M[j] = (E[j] & 0x007F007Fu) | cM;
            } else {
                E[j] = __float_as_uint(ex2(S[2 * j]));
                M[j] = __float_as_uint(ex2(S[2 * j + 1]));
            }
        }
#pragma unroll
        for (int j = (k - 1) * GRP; j >= 0 && j < k * GRP; j++)
            P[j >> 2][j & 3] = is_poly(j) ? hfma_bf(E[j], M[j], E[j] - M[j]) : pk_bf(__uint_as_float(E[j]), __uint_as_float(M[j]));
    }
}
__device__ __forceinline__ void pv_tile(float (&o)[12], uint32_t (&P)[4][4], uint64_t dv) {
#pragma unroll
    for (int j = 0; j < 4; j++) mma_pv(o, P[j], dv + j * 64);
}
__device__ __forceinline__ void mma16816(float (&d)[4], const uint32_t (&a)[4], uint32_t b0, uint32_t b1) {
    asm volatile("mma.sync.aligned.m16n8k16.row.col.f32.bf16.bf16.f32 {%0,%1,%2,%3}, {%4,%5,%6,%7}, {%8,%9}, {%0,%1,%2,%3};"
                 : "+f"(d[0]), "+f"(d[1]), "+f"(d[2]), "+f"(d[3]) : "r"(a[0]), "r"(a[1]), "r"(a[2]), "r"(a[3]), "r"(b0), "r"(b1));
}
__device__ __forceinline__ uint32_t trans8(uint32_t a) { uint32_t d; asm volatile("movmatrix.sync.aligned.m8n8.trans.b16 %0, %1;" : "=r"(d) : "r"(a)); return d; }

__device__ __forceinline__ bool q_not_f16(unsigned qn) { const float v = __uint_as_float(qn); return !(v <= 1048576.f && v >= 0.000244140625f); }
__device__ __noinline__ void attn_fallback(float* r, const uint4 qv, const uint4* kp, const uint8_t* vp) {
    const int lane = threadIdx.x & 31;
    const uint32_t q[4] = {qv.x, qv.y, qv.z, qv.w};
    float o0[4] = {0.f, 0.f, 0.f, 0.f}, o1[4] = {0.f, 0.f, 0.f, 0.f};
    float m0 = -3.0e38f, m1 = -3.0e38f, l0 = 0.f, l1 = 0.f;
#pragma unroll 1
    for (int i = 0; i < 128; i++) {
        const uint4 kk = __ldcg(kp + (i >> 3) * 8192 + (i & 7) * 32 + lane);
        const uint8_t* v = vp + i * 2048 + lane * 4;
        const uint32_t k00 = trans8(kk.x), k01 = trans8(kk.y), k10 = trans8(kk.z), k11 = trans8(kk.w);
        const uint32_t v00 = __ldcg((const uint32_t*)v), v01 = __ldcg((const uint32_t*)(v + 512));
        const uint32_t v10 = __ldcg((const uint32_t*)(v + 256)), v11 = __ldcg((const uint32_t*)(v + 768));
        float s0[4] = {0.f, 0.f, 0.f, 0.f}, s1[4] = {0.f, 0.f, 0.f, 0.f};
        mma16816(s0, q, k00, k01);
        mma16816(s1, q, k10, k11);
        float a = fmaxf(fmaxf(s0[0], s0[1]), fmaxf(s1[0], s1[1])), b = fmaxf(fmaxf(s0[2], s0[3]), fmaxf(s1[2], s1[3]));
        a = fmaxf(a, __shfl_xor_sync(0xffffffffu, a, 1)); a = fmaxf(a, __shfl_xor_sync(0xffffffffu, a, 2));
        b = fmaxf(b, __shfl_xor_sync(0xffffffffu, b, 1)); b = fmaxf(b, __shfl_xor_sync(0xffffffffu, b, 2));
        const float n0 = fmaxf(m0, a), n1 = fmaxf(m1, b);
        const float c0 = ex2(m0 - n0), c1 = ex2(m1 - n1);
        m0 = n0; m1 = n1;
        uint32_t p[4];
        p[0] = pk_bf(ex2(s0[0] - n0), ex2(s0[1] - n0)); p[1] = pk_bf(ex2(s0[2] - n1), ex2(s0[3] - n1));
        p[2] = pk_bf(ex2(s1[0] - n0), ex2(s1[1] - n0)); p[3] = pk_bf(ex2(s1[2] - n1), ex2(s1[3] - n1));
        l0 = l0 * c0 + (bf_lo(p[0]) + bf_hi(p[0]) + bf_lo(p[2]) + bf_hi(p[2]));
        l1 = l1 * c1 + (bf_lo(p[1]) + bf_hi(p[1]) + bf_lo(p[3]) + bf_hi(p[3]));
        o0[0] *= c0; o0[1] *= c0; o0[2] *= c1; o0[3] *= c1;
        o1[0] *= c0; o1[1] *= c0; o1[2] *= c1; o1[3] *= c1;
        mma16816(o0, p, v00, v10);
        mma16816(o1, p, v01, v11);
    }
    r[0] = o0[0]; r[1] = o0[1]; r[2] = o0[2]; r[3] = o0[3];
    r[4] = o1[0]; r[5] = o1[1]; r[6] = o1[2]; r[7] = o1[3];
    r[8] = quad_sum(l0); r[9] = quad_sum(l1);
}

__device__ __forceinline__ unsigned max_norm2(const float (&acc)[64], int lane) {
    unsigned mx = 0;
#pragma unroll
    for (int h = 0; h < 2; h++) {
        float nn[16];
#pragma unroll
        for (int e = 0; e < 16; e++) { const float* z = acc + h * 32 + (e >> 1) * 4 + (e & 1); nn[e] = fmaf(z[0], z[0], z[2] * z[2]); }
#pragma unroll
        for (int e = 0; e < 8; e++) nn[e] = ((lane & 16) ? nn[e + 8] : nn[e]) + __shfl_xor_sync(0xffffffffu, (lane & 16) ? nn[e] : nn[e + 8], 16);
#pragma unroll
        for (int e = 0; e < 4; e++) nn[e] = ((lane & 8) ? nn[e + 4] : nn[e]) + __shfl_xor_sync(0xffffffffu, (lane & 8) ? nn[e] : nn[e + 4], 8);
#pragma unroll
        for (int e = 0; e < 2; e++) nn[e] = ((lane & 4) ? nn[e + 2] : nn[e]) + __shfl_xor_sync(0xffffffffu, (lane & 4) ? nn[e] : nn[e + 2], 4);
        mx = max(mx, max(__float_as_uint(nn[0]), __float_as_uint(nn[1])));
    }
    return __reduce_max_sync(0xffffffffu, mx);
}
__device__ __forceinline__ void ln2_load(uint4 (&p)[4], const uint4* st) { p[0] = ld_ll128(st); p[1] = ld_ll128(st + 64); p[2] = ld_ll128(st + 128); p[3] = ld_ll128(st + 192); }
__device__ __forceinline__ uint4 ln2_rows(uint4 (&p)[4], const uint4* st, int t) {
    while (__any_sync(0xffffffffu, max(max(p[0].x, p[1].x), max(p[2].x, p[3].x)) == ~0u)) ln2_load(p, st);
    uint32_t r[4];
#pragma unroll
    for (int h = 0; h < 2; h++) {
        float s = 0.f, q = 0.f;
#pragma unroll
        for (int e = 0; e < 4; e++) { s += __uint_as_float(h ? p[e].z : p[e].x); q += __uint_as_float(h ? p[e].w : p[e].y); }
        const float mean = quad_sum(s) * (1.f / 512.f);
        const float var = fmaxf(quad_sum(q) * (1.f / 512.f) - mean * mean, 0.f) + 1e-5f;
        const float rs = rsqrtf(var), z = t < 2 ? -mean : var * rs, zh = bf_round(z);
        r[h] = __float_as_uint(0.5f * rs);
        r[2 + h] = pk_bf(zh, z - zh);
    }
    return make_uint4(r[0], r[1], r[2], r[3]);
}
template <int NJ>
__device__ __forceinline__ void ffn_epilogue(const float (&acc)[8 * NJ], uint8_t* dst, float a0, float a1, unsigned pace) {
#pragma unroll
    for (int j = 0; j < NJ; j++) {
        float r[4];
#pragma unroll
        for (int e = 0; e < 4; e++) {
            const float aa = e < 2 ? a0 : a1, u = aa * acc[4 * NJ + 4 * j + e];
            float th;
            asm("tanh.approx.f32 %0, %1;" : "=f"(th) : "f"(aa * acc[4 * j + e]));
            r[e] = fmaf(u, th, u);
        }
        uint8_t* d = dst + (j >> 1) * 4096 + (j & 1) * 128;
        *(uint32_t*)d = pk_bf(r[0], r[1]);
        *(uint32_t*)(d + 256) = pk_bf(r[2], r[3]);
        if (j < NJ - 1 && pace) __nanosleep(pace);
    }
}

__device__ __forceinline__ void gemv64(float (&d)[8][4], const uint8_t* w, int pitch, int nk, uint32_t vec, uint32_t ring) {
    const int lane = threadIdx.x & 31;
    w += (size_t)(lane >> 3) * pitch + (lane & 7) * 16;
    const uint32_t st = ring + (lane >> 3) * 128, ld = ring + (lane & 15) * 128;
#pragma unroll 1
    for (int k = -5; k < nk; k++) {
        if (k + 5 < nk) {
#pragma unroll
            for (int i = 0; i < 4; i++)
                asm volatile("cp.async.cg.shared.global [%0], [%1], 16;" ::"r"(st + ((k + 5) % 6) * 2048 + i * 512 + (((lane & 7) ^ ((i * 4 + (lane >> 3)) & 7)) << 4)),
                             "l"(w + (size_t)((k + 5) * 16 + i * 4) * pitch) : "memory");
        }
        asm volatile("cp.async.commit_group;" ::: "memory");
        if (k < 0) continue;
        asm volatile("cp.async.wait_group 5;" ::: "memory");
        __syncwarp();
        uint32_t a[4] = {0, 0, 0, 0};
        if (lane < 8) { a[0] = lds32(vec + (lane >> 2) * 1024 + k * 32 + (lane & 3) * 4); a[2] = lds32(vec + (lane >> 2) * 1024 + k * 32 + 16 + (lane & 3) * 4); }
#pragma unroll
        for (int j = 0; j < 4; j++) {
            const uint4 bq = ldsm_t(ld + (k % 6) * 2048 + (((j * 2 + (lane >> 4)) ^ (lane & 7)) << 4));
            mma16816(d[2 * j], a, bq.x, bq.y);
            mma16816(d[2 * j + 1], a, bq.z, bq.w);
        }
        __syncwarp();
    }
}
__device__ __forceinline__ void helper_cta(const Params& P, uint8_t* smem, int hi, bf16 cv, unsigned ep) {
    const int tid = threadIdx.x, warp = tid >> 5, lane = tid & 31;
    bf16* vec = (bf16*)smem;
    float* red = (float*)(smem + 4096);
    const uint32_t ring = SB + 16384 + warp * 12288;
    vec[tid] = vec[512 + tid] = __float2bfloat16_rn(silu_bf(__bfloat162float(cv)));
    bar_sync(1, 512);
#pragma unroll 1
    for (int ph = 0; ph < 2; ph++) {
        float d[8][4];
#pragma unroll
        for (int j = 0; j < 32; j++) d[j >> 2][j & 3] = 0.f;
        if (ph == 0 || warp < 14)
            gemv64(d, ph == 0 ? (const uint8_t*)(P.wmod + (size_t)(warp >> 3) * 256 * 3072 + 1024 + hi * 512 + (warp & 7) * 64)
                              : (const uint8_t*)((hi < 2 ? P.wg : P.wu) + (hi & 1) * 896 + warp * 64),
                   ph == 0 ? 6144 : 3584, ph == 0 ? 16 : 32, SB + (ph == 0 ? (warp >> 3) * 512 : 0), ring);
        if (lane < 8) {
#pragma unroll
            for (int j = 0; j < 8; j++) *(float2*)&red[(lane >> 2) * 1024 + warp * 64 + j * 8 + (lane & 3) * 2] = make_float2(d[j][0], d[j][1]);
        }
        bar_sync(1, 512);
        if (ph == 0) {
            float s = bf_round(red[tid] + red[512 + tid]);
            if (hi == 2) s = 1.f + s;
            const bf16 r = __float2bfloat16_rn(s);
            if (hi == 1 || hi == 2) P.S->mod2[(2 - hi) * 512 + tid] = r;
            if (hi != 1) ((bf16*)(P.S->aux + (tid >> 6) * AUX_BYTES + 7168))[(hi == 0 ? 0 : hi - 1) * 64 + (tid & 63)] = r;
        } else {
#pragma unroll 1
            for (int i = tid; i < 1792; i += 512) {
                const int which = i >= 896, fh = i - which * 896, f = (hi & 1) * 896 + fh, cgf = f / 224;
                int fl = f - cgf * 224;
                if (cgf & 1) fl = fl < 32 ? fl + 192 : fl - 32;
                const int col = (fl >> 6) * 128 + (fl & 63) + (hi >> 1) * (fl < 192 ? 64 : 32);
                const float s = red[which * 1024 + fh], h = bf_round(s);
                *(uint2*)(P.S->aux + cgf * AUX_BYTES + col * 16 + which * 8) = make_uint2(pk_bf(h, h), pk_bf(s - h, s - h));
            }
        }
        bar_sync(1, 512);
        if (tid == 0) { fence_gpu(); st_flag(&P.S->flag[F_AUX * 32 + ph * 8 + hi], ep); }
        if (ph) break;
        if (tid < 32) { __syncwarp(); poll_flags<true>(&P.S->flag[F_AUX * 32], 4, ep); }
        bar_sync(1, 512);
        ((uint32_t*)vec)[tid] = __ldcg((const uint32_t*)P.S->mod2 + tid);
        bar_sync(1, 512);
    }
}

__device__ __forceinline__ void w_ring(const Params& P, int cg, int i0) {
    constexpr uint32_t bar = SB + SM_BAR;
    const int colw = cg * 224 + (cg & 1) * 32, coln = cg * 224 + ((cg & 1) ? 0 : 192);
    int slot = i0;
#pragma unroll 1
    for (int i = i0; i < 28; i += 2) {
        mbar_spin(bar + (i == 0 ? B_ATE + 1 : (i == 1 ? B_P3H : (i == 2 ? B_P3H : (i == 3 ? B_P3D : (i == 4 ? B_P3D : B_WE + i - 5))))) * 8, i == 0);
        if (elect()) {
            const uint32_t dst = SB + SM_RING + slot * 16384, fb = bar + (B_WF + i) * 8;
            if (i == 3) { mbar_expect(bar + B_AUX * 8, 7168); bulk_ld(SB + SM_AUX, P.S->aux + cg * AUX_BYTES, 7168, bar + B_AUX * 8); }
            mbar_expect(fb, 16384);
            if (i < 4) {
                const int k0 = i == 0 ? cg : (2 * i - 1 < cg ? 2 * i - 1 : 2 * i), k1 = 2 * i < cg ? 2 * i : 2 * i + 1;
                tma2d(dst, &P.tGn, fb, coln, k0 * 64);
                tma2d(dst + 8192, &P.tUn, fb, coln, k0 * 64);
                tma2d(dst + 4096, &P.tGn, fb, coln, k1 * 64);
                tma2d(dst + 12288, &P.tUn, fb, coln, k1 * 64);
            } else {
                const int ii = (i - 4) & 7, kb = ii == 0 ? cg : (ii - 1 < cg ? ii - 1 : ii);
                tma2d(dst, &P.tG, fb, colw + ((i - 4) >> 3) * 64, kb * 64);
                tma2d(dst + 8192, &P.tU, fb, colw + ((i - 4) >> 3) * 64, kb * 64);
            }
        }
        slot += slot >= 3 ? -3 : 2;
    }
}

template <bool EARLY>
__device__ __forceinline__ void p5_feed(const Params& P, int mi, int s0, int s1, int step) {
    constexpr uint32_t sb = SB, bar = SB + SM_BAR;
    const int cg = mi & 7;
    const uint8_t* act = P.S->act + (size_t)(mi >> 3) * 112 * 4096;
    const unsigned c0 = EARLY ? 0 : lds32(sb + SM_EP + 8) + G8 - 8 * TAU;
#pragma unroll 1
    for (int sv = s0; sv < s1; sv += step) {
        const int s = uni(sv), c = (s - 4) >> 3, u = (s - 4) & 7;
        const uint32_t da = sb + SM_R0 + (s & 7) * 16384, db = sb + SM_RING + ((s + 6) % 10) * 8192, fb = bar + (B_PF + s) * 8;
        const bool nar = EARLY && s < 4;
        const uint8_t* src = act + (nar ? s * 114688 + 49152 : u * 57344 + c * 16384);
        const int row = nar ? s * 448 + 192 : u * 224 + (u & 1) * 32 + c * 64;
        if (elect()) mbar_expect(fb, 24576);
        if (!EARLY) {
            mbar_spin(bar + (s < 12 ? B_WE + 27 : B_PL) * 8, 0);
            asm volatile("fence.proxy.async.global;" ::: "memory");
            while ((int)(now_clk() - c0) < s * TAU) {}
        }
        mbar_spin(bar + (EARLY ? B_WE + max(20 + s, 23 + (s >> 1)) : B_PE + s - 8) * 8, 0);
        if (elect()) {
            bulk_ld(da, src, nar ? 8192 : 16384, fb);
            if (nar) bulk_ld(da + 8192, src + 57344, 8192, fb);
            tma2d(db, &P.tD, fb, cg * 64, row);
        }
        __syncwarp();
        if (!(s & 1)) STAMP(56 + (s >> 1));
    }
}

__global__ void __launch_bounds__(640, 1) block_kernel(const __grid_constant__ Params P) {
    extern __shared__ __align__(1024) uint8_t smem[];
    constexpr uint32_t sb = SB, bar = SB + SM_BAR;
    const int b = blockIdx.x;
    const int hi = (b == 112 || b == 113) ? b - 112 : (b >= 130 ? b - 128 : -1);

    if (threadIdx.x >= 512) {
        asm volatile("setmaxnreg.dec.sync.aligned.u32 32;");
        if (hi >= 0) EXIT();
        IDS();
        if (elect()) {
            l2_prefetch(P.wmod + (size_t)(mi * 4 + w) * 3072, 2048);
#pragma unroll 2
            for (int i = w; i < B_NUM; i += 4) mbar_init(bar + i * 8, i < B_END ? 1 : 4 << ((i >= B_WE) + (i >= B_ATE)));
        }
        __syncwarp();
        trap_if((uint32_t)__cvta_generic_to_shared(smem) != SB);
        STAMP(25);
        if (warp != 16) asm volatile("bar.arrive 3, 640;" ::: "memory");
        if (warp == 19) {
            asm volatile("bar.arrive 2, 640;" ::: "memory");
            if (lane == 0) l2_prefetch(P.wqkv + (size_t)mi * 6144, 12288);
            if (lane < 12) asm volatile("prefetch.tensormap [%0];" ::"l"(&P.tKV + lane) : "memory");
            __syncwarp();
            mbar_wait(bar + B_YF * 8, 1000);
            mbar_wait(bar + (B_WE + 12 + 1) * 8, 0);
            rendezvous(P.S->time, mi, lds32(sb + SM_EP), ADEL);
            STAMP(39);
            if (lane == 0) sts32(sb + SM_EP + 8, now_clk());
            release(bar + B_Y * 8);
            mbar_wait(bar + B_END * 8, 0);
            EXIT();
        }
        if (warp == 16) {
            bar_sync(3, 640);
            if (elect())
                for (int i = 0; i < 1; i++) { mbar_expect(bar + (B_P1F + i) * 8, 16384); tma3d(sb + SM_RING + (i + 1) * 16384, &P.tKV, bar + (B_P1F + i) * 8, cg * 64, i * 128, 1); }
            __syncwarp();
        }
        bar_sync(2, 640);
        const unsigned ep = lds32(sb + SM_EP);
        if (warp == 16) {
#pragma unroll 1
            for (int i = 1; i < 12; i++) {
                if (i == 5) { mbar_spin(bar + B_GSD * 8, 0); mbar_spin(bar + (B_P1F + 2) * 8, 0); }
                if (i >= 6) mbar_spin(bar + (B_P1E + (i == 11 ? 6 : i - 6)) * 8, 0);
                if (i == 10) mbar_spin(bar + B_KSG * 8, 0);
                if (elect()) {
                    const uint32_t dst = sb + SM_RING + ((P1SLOT >> (4 * i)) & 7) * 16384, fb = bar + (B_P1F + i) * 8;
                    mbar_expect(fb, 16384);
                    if (i < 8) tma3d(dst, &P.tKV, fb, cg * 64 + (i >> 2) * 32, (i & 3) * 128, 1);
                    else tma3d(dst, &P.tQ, fb, 0, (i & 3) * 128, cg * 2);
                }
            }
#pragma unroll 1
            for (int j = 0; j < 32; j++) {
                if (j == 0 || j == 4) poll_flags(&P.S->flag[(F_KV + cg) * 32 + j * 2], 8, ep);
                if (j == 16) { mbar_spin(bar + B_KM * 8, 0); asm volatile("fence.proxy.async.global;" ::: "memory"); }
                if (j == 0) { STAMP(20); mbar_spin(bar + B_ONE * 8, 0); }
                if (j < 4) mbar_spin(bar + (B_P1E + 10 + (j >> 1)) * 8, 0);
                else mbar_spin(bar + (B_ATE + (j & 3)) * 8, ((j >> 2) - 1) & 1);
                if (elect()) {
                    const uint32_t fb = bar + (B_ATF + (j & 3)) * 8;
                    const int z = cg * 32 + (j & 24);
                    mbar_expect(fb, 16384);
                    tma3d(sb + SM_K + (j & 3) * 8192, &P.tAK, fb, 0, j & 7, z);
                    tma3d(sb + SM_V0 + (j & 3) * 4096, &P.tAV, fb, 256, j & 7, z);
                    tma3d(sb + SM_V0 + 16384 + (j & 3) * 4096, &P.tAV, fb, 384, j & 7, z);
                    if (j == 4 || j == 21) mbar_arrive(bar + (j == 4 ? B_STG : B_P1G) * 8);
                }
            }
        } else {
            if (warp == 17) {
                mbar_spin(bar + B_KST * 8, 0);
                if (lane == 0) { fence_gpu(); st_flag(&P.S->flag[(F_KV + cg) * 32 + rb], ep); mbar_arrive(bar + B_KSG * 8); STAMP(24); }
                __syncwarp();
                mbar_spin(bar + B_KP * 8, 0);
                mbar_spin(bar + B_STG * 8, 0);
                fence_async_smem();
                if (elect()) {
                    bulk_st(P.S->kv + (size_t)((cg * 2 + 1) * 16 + rb) * 16384, sb + SM_SCR, 16384);
                    bulk_st_wait();
                    bulk_st(P.S->kp + mi * 1024, sb + SM_R1, 16384);
                    bulk_st_wait();
                }
                __syncwarp();
                if (lane == 0) { fence_gpu(); st_flag(&P.S->flag[(F_KV + cg) * 32 + 16 + rb], ep); }
                __syncwarp();
                unsigned* gf = &P.S->flag[(F_GRP + (rb >> 1)) * 32 + (mi & 15)];
#pragma unroll 1
                for (int i = 0; i < 5; i++) {
                    if (i == 0) mbar_nap(bar + B_SEN * 8);
                    if (i < 2) mbar_nap(bar + (i ? B_OD + 1 : B_OD) * 8);
                    mbar_spin(bar + (i == 0 ? B_OD : (i == 1 ? B_YD : B_ACT + i - 2)) * 8, 0);
                    if (i != 2 && lane == 0) { fence_gpu(); st_flag(gf + (i < 2 ? 0 : 16), ep * 4 + (i < 2 ? i : i - 2)); STAMP(i < 2 ? 54 + i : 33 + i); }
                    __syncwarp();
                    if (i == 1) {
                        release(bar + B_YF * 8);
                        poll_fast(gf - (mi & 15), 16, ep * 4 + 1);
                        asm volatile("fence.acquire.gpu;\nfence.proxy.async.global;" ::: "memory");
                        if (elect()) {
#pragma unroll
                            for (int k = 1; k < 8; k++) {
                                mbar_expect(bar + (B_Y + k) * 8, 16384);
                                bulk_ld(sb + SM_R0 + k * 16384, P.S->y + (size_t)(rb * 8 + (k - 1 < cg ? k - 1 : k)) * 16384, 16384, bar + (B_Y + k) * 8);
                            }
                        }
                        __syncwarp();
                        STAMP(22);
                    }
                }
                EXIT();
            }
            mbar_nap(bar + B_STG * 8);
            __nanosleep(1000);
            if (lane == 0) { st_ll64(&P.S->time[mi], 0, 0); st_flag(&P.S->flag[(F_GRP + (rb >> 1)) * 32 + 16 + (mi & 15)], ep * 4); }
            poll_flags(&P.S->flag[(F_KV + cg) * 32 + 16], 16, ep);
            {
                uint4 a = __ldcg((const uint4*)(P.S->nrm + cg * 128) + lane);
#pragma unroll
                for (int d = 2; d < 32; d <<= 1) {
                    a.x = max(a.x, __shfl_xor_sync(0xffffffffu, a.x, d)); a.y = max(a.y, __shfl_xor_sync(0xffffffffu, a.y, d));
                    a.z = max(a.z, __shfl_xor_sync(0xffffffffu, a.z, d)); a.w = max(a.w, __shfl_xor_sync(0xffffffffu, a.w, d));
                }
                const int h = (lane & 1) * 2 + ((lane >> 1) & 1);
                const unsigned qn = lds32(sb + SM_R0 + 16384 + h * 4);
                const float qm = __uint_as_float(qn), km = __uint_as_float((lane & 2) ? a.y : a.x), vm = __uint_as_float((lane & 2) ? a.w : a.z);
                const bool ok = qm * km <= 3600.f && qm <= 1048576.f && km <= 1048576.f && vm <= 1.0e24f && vm >= 1.0e-18f;
                if (lane < 4) sts32(sb + SM_KM + h * 4, ok ? 0 : (q_not_f16(qn) ? 2 : 1));
            }
            warp_arrive(bar + B_KM * 8);
            STAMP(17);
#pragma unroll
            for (int i = 0; i < 8; i++) sts128(sb + SM_R0 + 32768 + i * 512 + lane * 16, ~0u, ~0u, ~0u, ~0u);
            fence_async_smem();
            __syncwarp();
            if (elect()) {
#pragma unroll 1
                for (int i = 0; i < 7; i++) {
                    bulk_st(i < 4 ? P.S->act + (size_t)mi * 57344 + 32768 + i * 4096 : (i < 6 ? P.S->o + (size_t)(128 + mi) * 8192 + (i - 4) * 4096 : (uint8_t*)P.S->stat + mi * 2048),
                            sb + SM_R0 + 32768, i < 6 ? 4096 : 2048);
                    if (i < 5) l2_prefetch(i == 0 ? P.wo + (size_t)mi * 2048 : P.wd + (size_t)mi * 7168 + (i - 1) * 1792, i == 0 ? 4096 : 3584);
                    if (150) __nanosleep(150);
                }
                bulk_st_wait();
            }
            warp_arrive(bar + B_SEN * 8);
            if (elect()) {
                mbar_expect(bar + B_WO * 8, 65536);
                tma2d(sb + SM_R1, &P.tWo, bar + B_WO * 8, cg * 64, 0);
                tma2d(sb + SM_R1 + 32768, &P.tWo, bar + B_WO * 8, cg * 64, 256);
            }
            mbar_nap(bar + B_P1G * 8);
            poll_flags(&P.S->flag[(F_GRP + (rb >> 1)) * 32 + (mi & 8)], 8, ep * 4);
            if (elect()) { mbar_expect(bar + B_O0 * 8, 65536); bulk_ld(sb + SM_R0, P.S->o + (size_t)rb * 65536, 65536, bar + B_O0 * 8); }
            mbar_nap(bar + B_O0 * 8);
            poll_flags(&P.S->flag[F_AUX * 32], 4, ep);
            if (elect()) {
                mbar_expect(bar + B_MV * 8, 16384 + 384);
                tma2d(sb + SM_XT, &P.tX, bar + B_MV * 8, cg * 64, rb * 128);
                bulk_ld(sb + SM_MV, P.S->aux + cg * AUX_BYTES + 7168, 384, bar + B_MV * 8);
            }
            poll_flags(&P.S->flag[F_AUX * 32 + 8], 4, ep);
            STAMP(29);
            if (mi == 0 && lane == 0) st_flag(P.S->epoch, ep);
            mbar_nap(bar + B_WF * 8);
        }
        w_ring(P, cg, warp != 16);
        const unsigned* gf = &P.S->flag[(F_GRP + (rb >> 1)) * 32 + 16 + (mi & 8)];
        poll_flags(gf, 8, ep * 4 + 1);
        p5_feed<true>(P, mi, warp != 16, 8, 2);
        if (warp == 16) { poll_flags(gf, 8, ep * 4 + 2); release(bar + B_PL * 8); }
        EXIT();
    }

    if (hi < 0) {
        IDS();
        mbar_init(bar + (B_X + warp) * 8, 1);
        if (lane == 0) st_ll64(&P.S->lnll[mi * 16 + warp], 0, 0);
        if (tid < 8 && !(tid & 1)) st_ll64(&P.S->modll[mi * 4 + (tid >> 1)], 0, 0);
        const uint8_t* xr = (const uint8_t*)P.x + (size_t)(mi * 16 + warp) * 1024 + lane * 16;
        const uint8_t* cr = lane < 4 ? (const uint8_t*)P.c + warp * 64 + lane * 16 : (const uint8_t*)P.S->epoch;
        const bf16* wr = P.wmod + (size_t)tid * 3072 + mi * 8;
        asm volatile("{.reg .pred p; setp.lt.u32 p, %2, 5; @p cp.async.cg.shared.global [%0], [%1], 16;}" ::"r"(sb + SM_C + warp * 80 + lane * 16), "l"(cr), "r"(lane) : "memory");
        asm volatile("cp.async.cg.shared.global [%0], [%1], 16;\ncp.async.cg.shared.global [%0+8192], [%1+512], 16;\ncp.async.commit_group;" ::"r"(sb + SM_RING + 65536 + tid * 16), "l"(xr) : "memory");
        asm volatile("cp.async.cg.shared.global.L2::128B [%0], [%1], 16;" ::"r"(sb + SM_WM + tid * 16), "l"(wr) : "memory");
        asm volatile("cp.async.commit_group;" ::: "memory");
    }
    asm volatile("setmaxnreg.inc.sync.aligned.u32 112;");
    if (hi >= 0) { helper_cta(P, smem, hi, P.c[threadIdx.x], __ldcg(P.S->epoch) + 1); EXIT(); }

    {
        IDS();
        STAMP(23);
        if (P.hAux == 0) sched_fence();
        asm volatile("cp.async.wait_group 1;" ::: "memory");
        __syncwarp();
        const unsigned ep = lds32(sb + SM_C + warp * 80 + 64) + 1;
        const uint32_t c2 = lds32(sb + SM_C + warp * 80 + (lane >> 1) * 4);
        const float sc = silu_bf((lane & 1) ? bf_hi(c2) : bf_lo(c2));
        {
            const uint4 r0 = lds128(sb + SM_RING + 65536 + tid * 16), r1 = lds128(sb + SM_RING + 73728 + tid * 16);
            const uint32_t u[8] = {r0.x, r0.y, r0.z, r0.w, r1.x, r1.y, r1.z, r1.w};
            float s = 0.f, q = 0.f;
#pragma unroll
            for (int e = 0; e < 8; e++) { const float a = bf_lo(u[e]), c = bf_hi(u[e]); s += a + c; q = fmaf(a, a, fmaf(c, c, q)); }
#pragma unroll
            for (int d = 16; d; d >>= 1) { s += __shfl_xor_sync(0xffffffffu, s, d); q += __shfl_xor_sync(0xffffffffu, q, d); }
            const float mean = s * (1.f / 512.f), var = fmaxf(q * (1.f / 512.f) - mean * mean, 0.f);
            const float ve = bf_round(bf_round(var) + 1e-5f), rs = bf_round(rcp(bf_round(ve * rsqrtf(ve))));
            if (lane == 0) st_ll64(&P.S->lnll[mi * 16 + warp], pk_bf(rs, -mean * rs), ep);
        }
        STAMP(2);
        {
            asm volatile("cp.async.wait_group 0;" ::: "memory");
            if (elect()) { mbar_expect(bar + (B_X + warp) * 8, 8192); bulk_ld(sb + SM_R0 + warp * 8192, P.x + (size_t)(rb * 128 + warp * 8) * 512, 8192, bar + (B_X + warp) * 8); }
            const float s = sc;
            const uint4 wv = lds128(sb + SM_WM + tid * 16);
            float v[8] = {s * bf_lo(wv.x), s * bf_hi(wv.x), s * bf_lo(wv.y), s * bf_hi(wv.y), s * bf_lo(wv.z), s * bf_hi(wv.z), s * bf_lo(wv.w), s * bf_hi(wv.w)};
            const float r = reduce8(v, lane);
            if (t == 0) sts32(sb + SM_RED + (warp * 8 + g) * 4, __float_as_uint(r));
            if (tid == 0) sts32(sb + SM_EP, ep);
        }
        STAMP(26);
        bar_sync(1, 512);
        if (warp == 0) {
            float s = 0.f;
#pragma unroll
            for (int i = 0; i < 4; i++) s += __uint_as_float(lds32(sb + SM_RED + (((lane >> 3) * 4 + i) * 8 + (lane & 7)) * 4));
            s += __shfl_xor_sync(0xffffffffu, s, 8);
            s += __shfl_xor_sync(0xffffffffu, s, 16);
            s = bf_round(s);
            if (mi >= 64) s = 1.f + s;
            const float s1 = __shfl_down_sync(0xffffffffu, s, 1);
            if (lane < 8 && !(lane & 1)) st_ll64(&P.S->modll[mi * 4 + (lane >> 1)], pk_bf(s, s1), ep);
        }
        STAMP(1);
        const int wq = warp >> 2, hl = lane >> 4;
        uint2 st;
        do { st = ld_ll64(&P.S->lnll[rb * 128 + w * 32 + lane]); } while (!__all_sync(0xffffffffu, st.y == ep));
        uint4 xv[16];
        uint2 md;
#pragma unroll
        for (int i = 0; i < 16; i++) {
            if (!(i & 3)) mbar_spin(bar + (B_X + w * 4 + (i >> 2)) * 8, 0);
            if (i == 8) md = ld_ll64(&P.S->modll[tid]);
            if (i == 8) asm volatile("bar.arrive 3, 640;" ::: "memory");
            const uint32_t rr = __shfl_sync(0xffffffffu, st.x, 2 * i + hl), r2 = __byte_perm(rr, 0, 0x1010), o2 = __byte_perm(rr, 0, 0x3232);
            const uint4 u = lds128(sb + SM_R0 + (w * 32 + 2 * i + hl) * 1024 + wq * 256 + (lane & 15) * 16);
            xv[i] = make_uint4(hfma_bf(u.x, r2, o2), hfma_bf(u.y, r2, o2), hfma_bf(u.z, r2, o2), hfma_bf(u.w, r2, o2));
        }
#pragma unroll
        for (int i = 0; i < 16; i++) asm volatile("" : "+r"(xv[i].x), "+r"(xv[i].y), "+r"(xv[i].z), "+r"(xv[i].w));
        const uint32_t ha = (sb + SM_R0 + w * 32768 + (wq * 2 + ((lane >> 3) & 1)) * 1024 + hl * 128 + (lane & 7) * 16) ^ (hl << 4);
        sched_fence();
        STAMP(27);
        while (md.y != ep) md = ld_ll64(&P.S->modll[tid]);
        sts32(sb + SM_GS + tid * 4, md.x);
        bar_sync(2, 640);
        const uint4 sa = lds128(sb + SM_GS + wq * 256 + (lane & 15) * 16), ga = lds128(sb + SM_GS + 1024 + wq * 256 + (lane & 15) * 16);
        warp_arrive(bar + B_GSD * 8);
        STAMP(3);
        if (wq >= 1) {
#pragma unroll
            for (int i = 0; i < 16; i++) {
                xv[i] = make_uint4(hfma_bf(xv[i].x, ga.x, sa.x), hfma_bf(xv[i].y, ga.y, sa.y), hfma_bf(xv[i].z, ga.z, sa.z), hfma_bf(xv[i].w, ga.w, sa.w));
                asm volatile("" : "+r"(xv[i].x), "+r"(xv[i].y), "+r"(xv[i].z), "+r"(xv[i].w));
            }
            mbar_spin(bar + (B_HI + wq - 1) * 8, 0);
#pragma unroll
            for (int i = 0; i < 16; i++) sts128((ha ^ ((i & 3) << 5)) + (i >> 2) * 8192 + (i & 3) * 256, xv[i].x, xv[i].y, xv[i].z, xv[i].w);
        } else {
#pragma unroll
            for (int i = 0; i < 16; i++)
                sts128((ha ^ ((i & 3) << 5)) + (i >> 2) * 8192 + (i & 3) * 256, hfma_bf(xv[i].x, ga.x, sa.x), hfma_bf(xv[i].y, ga.y, sa.y), hfma_bf(xv[i].z, ga.z, sa.z), hfma_bf(xv[i].w, ga.w, sa.w));
        }
        release(bar + (B_HI + wq) * 8);
        fence_async_smem();
        warp_arrive(bar + (B_H + wq) * 8);
        STAMP(4);
    }

    uint32_t q[1][4];
    constexpr uint32_t qx = sb + SM_R0;
    {
        IDS();
        const int wq = warp >> 2;
        if (wq < 3) {
            float acc[64];
            zero(acc);
            const uint32_t pb = bar + wq * 32;
            if (wq) mbar_spin(bar + (wq == 1 ? B_P1E + 2 : B_P1E + 6) * 8, 0);
#pragma unroll
            for (int i = 0; i < 4; i++) {
                const int slot = ((uint32_t)(P1SLOT >> (wq * 16)) >> (4 * i)) & 7;
                const uint64_t da = P.hSW64 + (dlo(SM_RING, 8192) + slot * 1024);
                mbar_spin(bar + (B_H + i) * 8, 0);
                mbar_spin(pb + (B_P1F + i) * 8, 0);
                wg_fence();
#pragma unroll
                for (int j = 0; j < 8; j++) mma_ss128t(acc, da + j * 64, P.hH + (i * 128 + (j >> 2) * 64 + (j & 3) * 2));
                wg_commit();
                wg_wait<1>();
                if (i > 0) release(pb + (B_P1E + i - 1) * 8);
            }
            uint8_t* gd = P.S->kv + (size_t)(cg * 32 + rb) * 16384 + lane * 4 + (w < 2 ? w * 256 : 768 + w * 128);
            asm volatile("" : "+l"(gd));
            sched_fence();
            wg_wait<0>();
            pin(acc);
            release(pb + (B_P1E + 3) * 8);
            STAMP(wq == 0 ? 5 : (wq == 1 ? 6 : 31));
            if (wq < 2) {
                const uint32_t sd = sb + SM_SCR + (lane & 7) * 16 + (w < 2 ? w * 256 + (lane >> 4) * 512 + (lane & 8) * 16 : 768 + w * 128 + (lane >> 4) * 256 + (lane & 8) * 64);
                const int o1 = w < 2 ? 128 : 512, o2 = w < 2 ? 512 : 256;
                if (wq) mbar_spin(bar + (B_P1E + 5) * 8, 0);
#pragma unroll
                for (int hh = 0; hh < 2; hh++) {
                    uint32_t r[4][4];
                    if (w < 2) {
#pragma unroll
                        for (int e = 0; e < 16; e++) {
                            const float* d = acc + hh * 32 + 2 * e;
                            r[e >> 2][e & 3] = (hh || e > 1) ? pk_h(d[0] - d[-4], d[1] - d[-3]) : pk_h(d[0], d[1]);
                        }
                    } else {
#pragma unroll
                        for (int e = 0; e < 16; e++) r[e >> 2][e & 3] = pk_bf(acc[hh * 32 + 2 * e], acc[hh * 32 + 2 * e + 1]);
                    }
                    if (wq) {
#pragma unroll
                        for (int s = 0; s < 4; s++) stsm(sd + (hh * 4 + s) * 2048, r[s][0], r[s][1], r[s][2], r[s][3]);
                    } else {
#pragma unroll
                        for (int e = 0; e < 4; e++)
                            asm volatile("st.global.u32 [%0], %1;\nst.global.u32 [%0+2048], %2;\nst.global.u32 [%0+4096], %3;\nst.global.u32 [%0+6144], %4;" ::"l"(gd + hh * 8192 + (e & 1) * o1 + (e >> 1) * o2),
                                         "r"(r[0][e]), "r"(r[1][e]), "r"(r[2][e]), "r"(r[3][e]) : "memory");
                    }
                }
                if (wq == 0) { warp_arrive(bar + B_KST * 8); STAMP(28); }
                sched_fence();
                const unsigned mx = max_norm2(acc, lane);
                if (lane == 0) P.S->nrm[cg * 128 + rb * 8 + warp] = __uint_as_float(mx);
                mbar_spin(bar + (B_P1E + 11) * 8, 0);
                if (w < 2) {
#pragma unroll
                    for (int s = 0; s < 8; s++) {
                        const float* d = acc + 8 * s;
                        sts128(sb + SM_R1 + (wq * 2 + w) * 4096 + s * 512 + lane * 16, pk_bf(d[0], d[1]), pk_bf(d[2], d[3]), pk_bf(d[4], d[5]), pk_bf(d[6], d[7]));
                    }
                }
                warp_arrive(bar + B_KP * 8);
            } else {
#pragma unroll
                for (int e = 0; e < 64; e++) acc[e] *= 0.36067376022224085f;
                mbar_spin(bar + (B_P1E + 11) * 8, 0);
#pragma unroll
                for (int s = 0; s < 8; s++) {
                    const float* d = acc + 8 * s;
                    stsm_t(qx + w * 4096 + s * 512 + lane * 16, pk_h(d[0], d[1]), pk_h(d[4], d[5]), pk_h(d[2], d[3]), pk_h(d[6], d[7]));
                }
                warp_arrive(bar + B_QX * 8);
                sched_fence();
                const unsigned qn = max_norm2(acc, lane);
                if (lane == 0) sts32(qx + 16384 + w * 4, qn);
                if (q_not_f16(qn)) {
#pragma unroll
                    for (int s = 0; s < 8; s++) {
                        const float* d = acc + 8 * s;
                        P.S->qb[(mi * 4 + w) * 256 + s * 32 + lane] = make_uint4(pk_bf(d[0], d[1]), pk_bf(d[4], d[5]), pk_bf(d[2], d[3]), pk_bf(d[6], d[7]));
                    }
                }
                __syncwarp();
                STAMP(30);
            }
        } else {
            mbar_spin(bar + (B_P1E + 7) * 8, 0);
            const uint32_t one = (tid & 1) ? 0 : 0x3F803F80u;
#pragma unroll
            for (int i = 0; i < 8; i++) sts128(sb + SM_ONES + i * 2048 + (tid & 127) * 16, one, one, one, one);
            fence_async_smem();
            warp_arrive(bar + B_ONE * 8);
        }
        mbar_spin(bar + B_QX * 8, 0);
        const uint4 a = ldsm(qx + tid * 16);
        q[0][0] = a.x; q[0][1] = a.y; q[0][2] = a.z; q[0][3] = a.w;
    }
    STAMP(7);

    {
        const uint32_t cM = P.cM;
        float o[12], S[32];
        zero(o);
#pragma unroll
        for (int j = 0; j < 16; j++) S[2 * j] = S[2 * j + 1] = is_poly(j) ? EXP_MAGIC : 0.f;
        {
            const uint64_t d0 = P.hK[0] + uni(rd_tid() >> 8) * 16;
            mbar_spin(bar + B_ATF * 8, 0);
            STAMP(8);
            pin(S); pin(q);
            wg_fence();
            mma_qk(S, q[0], d0);
            wg_commit();
            wg_wait<0>();
            pin(S);
        }
#pragma unroll 1
        for (int seg = 0; seg < 4; seg++) {
            const uint32_t nu = uni(rd_tid() >> 8);
            const uint64_t dK[2] = {P.hK[0] + nu * 16, P.hK[1] + nu * 16}, dV[2] = {P.hV[0] + nu * 8, P.hV[1] + nu * 8};
            uint32_t Pa[4][4], Pb[4][4];
#pragma unroll
            for (int s = 0; s < 8; s++) {
                exp_tile(S, Pa, cM);
                pin(Pa); pin(S);
                wg_fence();
                mma_qk(S, q[0], dK[s >> 2] + ((s & 3) * 512 + 32));
                wg_commit();
                pv_tile(o, Pa, dV[s >> 2] + (s & 3) * 256);
                wg_commit();
                wg_wait<1>();
                pin(S);
                if (s > 0) release(bar + (B_ATE + ((s - 1) & 3)) * 8);
                if (s < 7) mbar_spin(bar + (B_ATF + ((s + 1) & 3)) * 8, ((s + 1) >> 2) & 1);
                else {
                    mbar_spin(bar + B_ATF * 8, seg == 3);
                    if (seg == 1) { const uint4 a = ldsm(qx + 8192 + rd_tid() * 16); q[0][0] = a.x; q[0][1] = a.y; q[0][2] = a.z; q[0][3] = a.w; }
                }
                exp_tile(S, Pb, cM);
                pin(Pb); pin(S);
                if (s == 7) {
#pragma unroll
                    for (int j = 0; j < 16; j++) S[2 * j] = S[2 * j + 1] = is_poly(j) ? EXP_MAGIC : 0.f;
                    pin(S); pin(q);
                }
                wg_fence();
                if (s < 7) { mma_qk(S, q[0], dK[((s + 1) >> 2) & 1] + ((s + 1) & 3) * 512); wg_commit(); }
                pv_tile(o, Pb, dV[s >> 2] + ((s & 3) * 256 + 16));
                wg_commit();
                if (s < 7) { wg_wait<1>(); pin(S); }
            }
            mma_qk(S, q[0], dK[0]);
            wg_commit();
            const int tid = rd_tid(), p = seg >> 1;
            unsigned bad = 0;
            if (seg & 1) {
                mbar_spin(bar + (p ? B_O0 : B_KM) * 8, 0);
                bad = lds32(sb + SM_KM + p * 8 + (tid >> 8) * 4);
            }
            uint8_t* od = P.S->o + (size_t)(p * 128 + rd_cta()) * 8192 + (p ? tid * 16 : tid * 4 + (tid >> 5) * 384);
            asm volatile("" : "+l"(od));
            sched_fence();
            wg_wait<0>();
            pin(o); pin(S);
            release(bar + (B_ATE + 3) * 8);
            if (!(seg & 1)) STAMP(70 + (seg >> 1));
            if (seg & 1) {
                if (bad) {
                    IDS();
                    float r[10];
                    uint4 qv;
                    if (bad & 2) { qv = __ldcg(&P.S->qb[(mi * 4 + p * 2 + n) * 256 + (tid & 255)]); qv = make_uint4(trans8(qv.x), trans8(qv.y), trans8(qv.z), trans8(qv.w)); }
                    else {
                        qv = p ? make_uint4(q[0][0], q[0][1], q[0][2], q[0][3]) : ldsm(qx + tid * 16);
                        uint32_t* u = &qv.x;
#pragma unroll
                        for (int e = 0; e < 4; e++) { const float2 f = __half22float2(*(const __half2*)&u[e]); u[e] = pk_bf(f.x, f.y); }
                    }
                    attn_fallback(r, qv, P.S->kp + (cg * 4 + p * 2 + n) * 256, P.S->kv + (size_t)(cg * 2 + p) * 262144 + 1024 + n * 128);
#pragma unroll
                    for (int e = 0; e < 8; e++) o[4 + e] = r[e];
                    o[0] = r[8]; o[2] = r[9];
                }
                const float i0 = rcp(o[0]), i1 = rcp(o[2]);
                const uint32_t o0 = pk_bf(o[4] * i0, o[5] * i0), o1 = pk_bf(o[8] * i0, o[9] * i0), o2 = pk_bf(o[6] * i1, o[7] * i1), o3 = pk_bf(o[10] * i1, o[11] * i1);
                if (p) st_ll128(od, o0, o2, o1, o3);
                else asm volatile("st.global.u32 [%0], %1;\nst.global.u32 [%0+128], %2;\nst.global.u32 [%0+256], %3;\nst.global.u32 [%0+384], %4;" ::"l"(od), "r"(o0), "r"(o1), "r"(o2), "r"(o3) : "memory");
                warp_arrive(bar + (B_OD + p) * 8);
                zero(o);
                STAMP(9 + p);
            }
        }
    }

    uint32_t x2[8];
    {
        IDS();
        float acc[32];
        zero(acc);
        const uint64_t dW = P.hSW128 + (dlo(SM_R1, 16) + n * 2048), dO = P.hCORE + (dlo(SM_R0, 128) + m * 128 + n * 2048);
        mbar_spin(bar + B_MV * 8, 0);
        mbar_spin(bar + B_WO * 8, 0);
        mbar_spin(bar + B_O0 * 8, 0);
        float ga[8];
        uint32_t cb[4];
#pragma unroll
        for (int j = 0; j < 4; j++) {
            const uint32_t u = lds32(sb + SM_MV + n * 64 + j * 16 + t * 4);
            ga[2 * j] = bf_lo(u); ga[2 * j + 1] = bf_hi(u);
            cb[j] = lds32(sb + SM_MV + 128 + n * 64 + j * 16 + t * 4);
        }
#pragma unroll
        for (int j = 0; j < 2; j++) {
            const uint4 u = ldsm(sb + SM_XT + (m * 64 + w * 16 + (lane & 15)) * 128 + (((n * 4 + j * 2 + (lane >> 4)) ^ (lane & 7)) << 4));
            x2[4 * j] = u.x; x2[4 * j + 1] = u.y; x2[4 * j + 2] = u.z; x2[4 * j + 3] = u.w;
        }
        const uint8_t* op = P.S->o + (size_t)(128 + rb * 8 + n * 4) * 8192 + (tid & 255) * 16;
        uint32_t of[8][4];
        wg_fence();
#pragma unroll
        for (int s = 0; s <= 8; s++) {
            if (s == 4) {
                sched_fence();
#pragma unroll
                for (int u = 0; u < 8; u++) { const uint4 v = ld_ll128(op + u * 4096); of[u][0] = v.x; of[u][1] = v.y; of[u][2] = v.z; of[u][3] = v.w; }
                sched_fence();
                if (s < 8) wg_fence();
            }
            if (s < 8) mma_ss64(acc, dO + s * 256, dW + ((s >> 1) * 512 + (s & 1) * 128));
            if (s == 7) wg_commit();
        }
        sched_fence();
        wg_wait<0>();
        pin(acc);
        release(bar + B_P3H * 8);
        sched_fence();
        while (true) {
            unsigned mx = 0;
#pragma unroll
            for (int s = 0; s < 8; s++) mx = max(mx, of[s][0]);
            if (!__any_sync(0xffffffffu, mx == ~0u)) break;
#pragma unroll
            for (int s = 0; s < 8; s++)
                if (of[s][0] == ~0u) { const uint4 v = ld_ll128(op + s * 4096); of[s][0] = v.x; of[s][1] = v.y; of[s][2] = v.z; of[s][3] = v.w; }
        }
        STAMP(21);
        pin(of);
        wg_fence();
#pragma unroll
        for (int s = 0; s < 8; s++) mma_rs64t(acc, of[s], dW + ((s >> 1) * 512 + 256 + (s & 1) * 128));
        wg_commit();
        mbar_spin(bar + B_P3H * 8, 0);
        const uint32_t xs = sb + SM_R0 + 32768 + (tid & 255) * 16, ys = sb + SM_R0 + n * 8192 + tile + lane * 16;
        uint32_t* yd = (uint32_t*)(P.S->y + (size_t)mi * 16384 + n * 8192 + tile) + lane;
        asm volatile("" : "+l"(yd));
        sched_fence();
        wg_wait<0>();
        pin(acc);
        release(bar + B_P3D * 8);
        STAMP(11);
        float v[16];
        if (n) {
#pragma unroll
            for (int j = 0; j < 4; j++) sts128(xs + j * 4096, __float_as_uint(acc[4 * j]), __float_as_uint(acc[4 * j + 1]), __float_as_uint(acc[4 * j + 2]), __float_as_uint(acc[4 * j + 3]));
#pragma unroll
            for (int j = 0; j < 16; j++) v[j] = fmaf(ga[(j >> 2) * 2 + (j & 1)], acc[16 + j], (j & 1) ? bf_hi(x2[j >> 1]) : bf_lo(x2[j >> 1]));
        } else {
#pragma unroll
            for (int j = 4; j < 8; j++) sts128(xs + j * 4096, __float_as_uint(acc[4 * j]), __float_as_uint(acc[4 * j + 1]), __float_as_uint(acc[4 * j + 2]), __float_as_uint(acc[4 * j + 3]));
#pragma unroll
            for (int j = 0; j < 16; j++) v[j] = fmaf(ga[(j >> 2) * 2 + (j & 1)], acc[j], (j & 1) ? bf_hi(x2[j >> 1]) : bf_lo(x2[j >> 1]));
        }
        pin(v);
        sched_fence();
        bar_sync(6 + m, 256);
        uint4 r[4];
#pragma unroll
        for (int j = 0; j < 4; j++) r[j] = lds128(xs + n * 16384 + j * 4096);
        uint32_t y[8];
#pragma unroll
        for (int j = 0; j < 4; j++) {
            v[4 * j] = fmaf(ga[2 * j], __uint_as_float(r[j].x), v[4 * j]);
            v[4 * j + 1] = fmaf(ga[2 * j + 1], __uint_as_float(r[j].y), v[4 * j + 1]);
            v[4 * j + 2] = fmaf(ga[2 * j], __uint_as_float(r[j].z), v[4 * j + 2]);
            v[4 * j + 3] = fmaf(ga[2 * j + 1], __uint_as_float(r[j].w), v[4 * j + 3]);
            x2[2 * j] = pk_bf(v[4 * j], v[4 * j + 1]);
            x2[2 * j + 1] = pk_bf(v[4 * j + 2], v[4 * j + 3]);
            y[2 * j] = hmul_bf(x2[2 * j], cb[j]);
            y[2 * j + 1] = hmul_bf(x2[2 * j + 1], cb[j]);
            asm volatile("st.global.u32 [%0], %1;\nst.global.u32 [%0+256], %2;" ::"l"(yd + (j >> 1) * 1024 + (j & 1) * 32), "r"(y[2 * j]), "r"(y[2 * j + 1]) : "memory");
        }
        warp_arrive(bar + B_YD * 8);
        STAMP(12);
        sched_fence();
        stsm(ys, y[0], y[2], y[1], y[3]);
        stsm(ys + 4096, y[4], y[6], y[5], y[7]);
        float s0 = 0.f, s1 = 0.f, q0 = 0.f, q1 = 0.f;
#pragma unroll
        for (int j = 0; j < 4; j++) {
            s0 += v[4 * j] + v[4 * j + 1]; s1 += v[4 * j + 2] + v[4 * j + 3];
            q0 = fmaf(v[4 * j], v[4 * j], fmaf(v[4 * j + 1], v[4 * j + 1], q0));
            q1 = fmaf(v[4 * j + 2], v[4 * j + 2], fmaf(v[4 * j + 3], v[4 * j + 3], q1));
        }
        s0 = quad_sum(s0); s1 = quad_sum(s1); q0 = quad_sum(q0); q1 = quad_sum(q1);
        if (t == 0) st_ll128(&P.S->stat[mi * 128 + (tid >> 2)], __float_as_uint(s0), __float_as_uint(q0), __float_as_uint(s1), __float_as_uint(q1));
        sched_fence();
        fence_async_smem();
        warp_arrive(bar + B_YS * 8);
        mbar_spin(bar + B_YS * 8, 0);
    }
    int c = 0;
    uint4 ab = make_uint4(0, 0, 0, 0);
    if (uni(rd_tid() >> 8) == 0) {
        IDS();
        c = 1;
        const uint64_t dY = P.hCORE + (dlo(SM_R0, 128) + m * 128);
        uint4 sp[4];
        const uint4* strow = &P.S->stat[(rb * 8 + t * 2) * 128 + (tid >> 2)];
        uint32_t fa[1][4];
        float acc[32];
        zero(acc);
#pragma unroll
        for (int i = 0; i < 8; i++) {
            if (!(i & 1)) mbar_spin(bar + (B_WF + (i >> 1)) * 8, 0);
            if (i) mbar_spin(bar + (B_Y + i) * 8, 0);
            wg_fence();
#pragma unroll
            for (int j = 0; j < 4; j++) mma_ss64(acc, dY + (i * 1024 + j * 256), P.hSW64 + (dlo(SM_RING, 8192) + (i >> 1) * 1024 + (i & 1) * 256 + j * 64));
            wg_commit();
            wg_wait<1>();
            if (i > 0 && !(i & 1)) release(bar + (B_WE + (i >> 1) - 1) * 8);
            if (i == 0) { mbar_spin(bar + (B_Y + 1) * 8, 0); ln2_load(sp, strow); sched_fence(); }
            if (i == 7) { wg_wait<0>(); release(bar + (B_WE + 3) * 8); sched_fence(); }
            if (i == 7) {
                ab = ln2_rows(sp, strow, t);
                sts128(sb + SM_AB + tid * 16, ab.x, ab.y, ab.z, ab.w);
                mbar_spin(bar + B_AUX * 8, 0);
                warp_arrive(bar + B_AB * 8);
            }
        }
        fa[0][0] = ab.z; fa[0][1] = ab.w; fa[0][2] = fa[0][3] = 0;
        pin(fa);
        wg_fence();
        mma_rs64(acc, fa[0], P.hAux + 384);
        wg_commit();
        wg_wait<0>();
        pin(acc);
        MARK(16);
        ffn_epilogue<4>(acc, P.S->act + (size_t)mi * 57344 + 49152 + tile + lane * 4, __uint_as_float(ab.x), __uint_as_float(ab.y), PACE);
        warp_arrive(bar + B_ACT * 8);
        MARK(35);
    }

#pragma unroll 1
    for (; c < 3; c += 2) {
        float acc[64];
        zero(acc);
        const int cu = uni(c);
        const uint64_t dY = P.hCORE + uni(dlo(SM_R0, 128) + (rd_tid() & 128));
        const uint32_t wb = bar + cu * 64;
        uint32_t fa[1][4];
        if (cu == 2) mbar_spin(bar + B_Y * 8, 0);
        if (cu) mbar_spin(wb + (B_WE - 4 + 5) * 8, 0);
#pragma unroll
        for (int i = 0; i < 8; i++) {
            int slot = (i + 4) % 5 + 5 - 2 * cu;
            if (slot >= 5) slot -= 5;
            if (i) mbar_spin(bar + (B_Y + i) * 8, 0);
            mbar_spin(wb + (B_WF + 4 + i) * 8, 0);
            MARK(72 + cu * 8 + i);
            const uint64_t db = P.hSW128 + (dlo(SM_RING, 8192) + slot * 1024);
            wg_fence();
#pragma unroll
            for (int j = 0; j < 4; j++) mma_ss128(acc, dY + (i * 1024 + j * 256), db + j * 128);
            wg_commit();
            wg_wait<1>();
            if (i > 0) release(wb + (B_WE + 3 + i) * 8);
            if (i == 7 && cu == 0) { mbar_spin(bar + B_AB * 8, 0); ab = lds128(sb + SM_AB + (rd_tid() & 255) * 16); }
        }
        fa[0][0] = ab.z; fa[0][1] = ab.w; fa[0][2] = fa[0][3] = 0;
        pin(fa);
        wg_fence();
        mma_rs128(acc, fa[0], P.hAux + cu * 128);
        wg_commit();
        wg_wait<1>();
        release(wb + (B_WE + 11) * 8);
        wg_wait<0>();
        pin(acc);
        MARK(13 + c);
        IDS();
        ffn_epilogue<8>(acc, P.S->act + (size_t)mi * 57344 + cu * 16384 + tile + lane * 4, __uint_as_float(ab.x), __uint_as_float(ab.y), cu == 0 ? PACE : (cu == 1 ? 0 : PACE2));
        warp_arrive(bar + (B_ACT + 1 + c) * 8);
        MARK(32 + c);
    }
    IDS();
    mbar_spin(bar + (B_ACT + (n ? 3 : 1)) * 8, 0);
#pragma unroll
    for (int j = 0; j < 2; j++) stsm(sb + SM_SCR + ((n * 2 + j) ^ 2) * 4096 + tile + lane * 16, x2[4 * j], x2[4 * j + 2], x2[4 * j + 1], x2[4 * j + 3]);
    warp_arrive(bar + B_X2 * 8);
    if (n == 1) {
        {
            const int u = warp & 7;
            const uint32_t dst = sb + SM_R0 + (u ^ 4) * 16384;
            mbar_spin(bar + (B_PF + 20 + u) * 8, 0);
            unsigned mx = 0;
#pragma unroll
            for (int e = 0; e < 16; e++) mx = max(mx, lds32(dst + e * 1024 + lane * 32 + g * 4));
            if (__any_sync(0xffffffffu, mx == ~0u)) {
#pragma unroll 1
                for (int e = 0; e < 32;) {
                    uint4 v[8];
                    mx = 0;
#pragma unroll
                    for (int i = 0; i < 8; i++) v[i] = ld_ll128(P.S->act + (size_t)(rb * 8 + u) * 57344 + 32768 + (e + i) * 512 + lane * 16);
#pragma unroll
                    for (int i = 0; i < 8; i++) { mx = max(max(mx, v[i].x), max(max(v[i].y, v[i].z), v[i].w)); sts128(dst + (e + i) * 512 + lane * 16, v[i].x, v[i].y, v[i].z, v[i].w); }
                    if (mx != ~0u) e += 8;
                }
                fence_async_smem();
                STAMP(38);
            }
            __syncwarp();
            if (lane < 4) mbar_arrive(bar + (B_AV + u) * 8);
        }
        EXIT();
    }
    if (m == 1) {
        mbar_spin(bar + B_PF * 8, 0);
        asm volatile("fence.proxy.async.global;" ::: "memory");
        p5_feed<false>(P, mi, 8 + w, 28, 4);
        EXIT();
    }

    {
        float acc[64];
        zero(acc);
        const uint32_t gu0 = lds32(sb + SM_MV + 256 + w * 32 + (g >> 1) * 4), gu1 = lds32(sb + SM_MV + 272 + w * 32 + (g >> 1) * 4);
        const float gb0 = (g & 1) ? bf_hi(gu0) : bf_lo(gu0), gb1 = (g & 1) ? bf_hi(gu1) : bf_lo(gu1);
        mbar_spin(bar + (B_WE + 26) * 8, 0);
        int slot = 6;
#pragma unroll 1
        for (int s = 0; s < 28; s += 2) {
            const uint32_t su = uni(s);
            const uint64_t da = P.hSW128 + uni(dlo(SM_RING, 16) + slot * 512), db = P.hCORE + (dlo(SM_R0, 128) + (su & 7) * 1024);
            const uint32_t pb = bar + su * 8;
            slot = slot == 8 ? 0 : slot + 2;
#pragma unroll
            for (int u = 0; u < 2; u++) {
                mbar_spin(pb + ((su < 20 ? B_PF : B_AV - 20) + u) * 8, 0);
                if (!u) MARK(40 + (s >> 1));
                wg_fence();
#pragma unroll
                for (int j = 0; j < 4; j++) mma_ss128t(acc, da + (u * 512 + j * 128), db + (u * 1024 + j * 256));
                wg_commit();
                wg_wait<1>();
                if ((u || su) && su < 22) release(pb + (B_PE + u - 1) * 8);
            }
        }
        uint4 xr[8];
        mbar_spin(bar + B_X2 * 8, 0);
#pragma unroll
        for (int j = 0; j < 4; j++) xr[j] = ldsm_t(sb + SM_SCR + (w ^ 2) * 4096 + j * 512 + lane * 16);
        wg_wait<0>();
        pin(acc);
#pragma unroll
        for (int j = 4; j < 8; j++) xr[j] = ldsm_t(sb + SM_SCR + (w ^ 2) * 4096 + j * 512 + lane * 16);
        sched_fence();
        release(bar + B_END * 8);
        MARK(18);
        const uint32_t od = sb + SM_R0 + 5 * 16384 + ((lane >> 4) * 8 + (lane & 7)) * 128 + (((w * 2 + ((lane >> 3) & 1)) ^ (lane & 7)) << 4);
#pragma unroll
        for (int j = 0; j < 8; j++) {
            const float* d = acc + 8 * j;
            stsm_t(od + j * 2048, pk_bf(fmaf(gb0, d[0], bf_lo(xr[j].x)), fmaf(gb0, d[1], bf_hi(xr[j].x))), pk_bf(fmaf(gb1, d[2], bf_lo(xr[j].y)), fmaf(gb1, d[3], bf_hi(xr[j].y))),
                   pk_bf(fmaf(gb0, d[4], bf_lo(xr[j].z)), fmaf(gb0, d[5], bf_hi(xr[j].z))), pk_bf(fmaf(gb1, d[6], bf_lo(xr[j].w)), fmaf(gb1, d[7], bf_hi(xr[j].w))));
            if ((j & 3) == 3) {
                fence_async_smem();
                bar_sync(4, 128);
                if (tid == 0)
                    asm volatile("cp.async.bulk.tensor.2d.global.shared::cta.bulk_group [%0, {%2, %3}], [%1];" ::"l"(&P.tOut), "r"(sb + SM_R0 + 5 * 16384 + (j >> 2) * 8192), "r"(cg * 64), "r"(rb * 128 + (j >> 2) * 64) : "memory");
                if (j == 3) { pin(acc); sched_fence(); }
            }
        }
        if (tid == 0) asm volatile("cp.async.bulk.commit_group;\ncp.async.bulk.wait_group.read 0;" ::: "memory");
    }
}

typedef CUresult (*EncodeFn)(CUtensorMap*, CUtensorMapDataType, cuuint32_t, void*, const cuuint64_t*, const cuuint64_t*, const cuuint32_t*,
                             const cuuint32_t*, CUtensorMapInterleave, CUtensorMapSwizzle, CUtensorMapL2promotion, CUtensorMapFloatOOBfill);

static void map2d(EncodeFn enc, CUtensorMap* tm, const void* p, int cols, int rows, int bc, int br, CUtensorMapSwizzle sw) {
    cuuint64_t gd[2] = {(cuuint64_t)cols, (cuuint64_t)rows}, gs[1] = {(cuuint64_t)cols * 2};
    cuuint32_t box[2] = {(cuuint32_t)bc, (cuuint32_t)br}, es[2] = {1, 1};
    enc(tm, CU_TENSOR_MAP_DATA_TYPE_BFLOAT16, 2, (void*)p, gd, gs, box, es, CU_TENSOR_MAP_INTERLEAVE_NONE, sw, CU_TENSOR_MAP_L2_PROMOTION_L2_128B,
        CU_TENSOR_MAP_FLOAT_OOB_FILL_NONE);
}

extern "C" void kernel_launch(void* const* d_in, const int* in_sizes, int n_in, void* d_out, int out_size) {
    (void)in_sizes; (void)n_in; (void)out_size;
    EncodeFn enc = nullptr;
    cudaDriverEntryPointQueryResult qr;
    cudaGetDriverEntryPoint("cuTensorMapEncodeTiled", (void**)&enc, cudaEnableDefault, &qr);
    Params P;
    P.x = (const bf16*)d_in[0]; P.wqkv = (const bf16*)d_in[1]; P.wo = (const bf16*)d_in[2];
    P.wg = (const bf16*)d_in[4]; P.wu = (const bf16*)d_in[5]; P.wd = (const bf16*)d_in[6];
    cudaGetSymbolAddress((void**)&P.S, g_scratch);
    P.c = (const bf16*)d_in[7]; P.wmod = (const bf16*)d_in[8];
    {
        cuuint64_t gd[3] = {512, 512, 3}, gs[2] = {3072, 1024};
        cuuint32_t box[3] = {32, 128, 2}, es[3] = {1, 1, 1};
        enc(&P.tKV, CU_TENSOR_MAP_DATA_TYPE_BFLOAT16, 3, (void*)P.wqkv, gd, gs, box, es, CU_TENSOR_MAP_INTERLEAVE_NONE, CU_TENSOR_MAP_SWIZZLE_64B,
            CU_TENSOR_MAP_L2_PROMOTION_L2_128B, CU_TENSOR_MAP_FLOAT_OOB_FILL_NONE);
        cuuint64_t qd[3] = {32, 512, 16}, qs[2] = {3072, 64};
        enc(&P.tQ, CU_TENSOR_MAP_DATA_TYPE_BFLOAT16, 3, (void*)P.wqkv, qd, qs, box, es, CU_TENSOR_MAP_INTERLEAVE_NONE, CU_TENSOR_MAP_SWIZZLE_64B,
            CU_TENSOR_MAP_L2_PROMOTION_L2_128B, CU_TENSOR_MAP_FLOAT_OOB_FILL_NONE);
    }
    {
        void* kv = (uint8_t*)P.S + offsetof(Scratch, kv);
        cuuint64_t gd[3] = {512, 8, 256}, gs[2] = {2048, 16384};
        cuuint32_t bk[3] = {256, 1, 8}, bv[3] = {128, 1, 8}, es[3] = {1, 1, 1};
        enc(&P.tAK, CU_TENSOR_MAP_DATA_TYPE_UINT32, 3, kv, gd, gs, bk, es, CU_TENSOR_MAP_INTERLEAVE_NONE, CU_TENSOR_MAP_SWIZZLE_NONE,
            CU_TENSOR_MAP_L2_PROMOTION_L2_128B, CU_TENSOR_MAP_FLOAT_OOB_FILL_NONE);
        enc(&P.tAV, CU_TENSOR_MAP_DATA_TYPE_UINT32, 3, kv, gd, gs, bv, es, CU_TENSOR_MAP_INTERLEAVE_NONE, CU_TENSOR_MAP_SWIZZLE_NONE,
            CU_TENSOR_MAP_L2_PROMOTION_L2_128B, CU_TENSOR_MAP_FLOAT_OOB_FILL_NONE);
    }
    map2d(enc, &P.tWo, P.wo, 512, 512, 64, 256, CU_TENSOR_MAP_SWIZZLE_128B);
    map2d(enc, &P.tX, P.x, 512, 2048, 64, 128, CU_TENSOR_MAP_SWIZZLE_128B);
    map2d(enc, &P.tG, P.wg, 1792, 512, 64, 64, CU_TENSOR_MAP_SWIZZLE_128B);
    map2d(enc, &P.tU, P.wu, 1792, 512, 64, 64, CU_TENSOR_MAP_SWIZZLE_128B);
    map2d(enc, &P.tGn, P.wg, 1792, 512, 32, 64, CU_TENSOR_MAP_SWIZZLE_64B);
    map2d(enc, &P.tUn, P.wu, 1792, 512, 32, 64, CU_TENSOR_MAP_SWIZZLE_64B);
    map2d(enc, &P.tD, P.wd, 512, 1792, 64, 64, CU_TENSOR_MAP_SWIZZLE_128B);
    map2d(enc, &P.tOut, d_out, 512, 2048, 64, 64, CU_TENSOR_MAP_SWIZZLE_128B);
    cudaFuncSetAttribute(block_kernel, cudaFuncAttributeMaxDynamicSharedMemorySize, SM_TOTAL);
    P.hSW128 = dhi(1024, 1); P.hSW64 = dhi(512, 2); P.hCORE = dhi(256, 0);
    P.hK[0] = P.hK[1] = dhi(1024, 0) + dlo(SM_K, 128); P.hV[0] = P.hV[1] = dhi(16384, 0) + dlo(SM_ONES, 512);
    P.hH = dhi(8192, 1) + dlo(SM_R0, 16); P.hAux = dhi(128, 0) + dlo(SM_AUX, 0);
    P.cM = 0x9F809F80u; P.pad = 0;
    block_kernel<<<132, 640, SM_TOTAL>>>(P);
}
```
